```python
import torch

def _softmax(x, axis=-1):
    return torch.softmax(x, dim=axis)
def _gelu(x):
    return torch.nn.functional.gelu(x, approximate="tanh")
def _silu(x):
    return torch.nn.functional.silu(x)
def _sigmoid(x):
    return torch.sigmoid(x)
def _layernorm(x, axis=-1, eps=1e-5):
    m = x.mean(dim=axis, keepdim=True)
    v = x.var(dim=axis, keepdim=True, unbiased=False)
    return (x - m) / torch.sqrt(v + eps)
def _scatter_add(tgt, idx, src, axis=0):
    return tgt.clone().index_add_(axis, idx, src)
def _segment_sum(src, seg, n):
    out = torch.zeros((n,) + src.shape[1:], dtype=src.dtype)
    return out.index_add_(0, seg, src)
def _pad(x, pw):
    flat = tuple(v for pair in reversed(pw) for v in pair)
    return torch.nn.functional.pad(x, flat)

kernel_name = 'parallel_sum__sliding_block_cached__geglu_ffn__decode'

def setup_inputs():

    _w = (lambda a: (lambda t: t.to(torch.bfloat16) if t.is_floating_point() else t)(torch.as_tensor(a)))
    def _A_setup():
        B, Sq, D = 4, 1, 448
        Hq, Hkv, Sk, Dh = 16, 8, 4096, 256
        assert Hq % Hkv == 0, (Hq, Hkv)
        return {
            "x": _w((lambda *s: torch.randn(*s, dtype=torch.bfloat16) * 0.05)(B, Sq, D)),
            "k_cache": _w((lambda *s: torch.randn(*s, dtype=torch.bfloat16) * 3.2)(B, Hkv, Sk, Dh)),
            "v_cache": _w((lambda *s: torch.randn(*s, dtype=torch.bfloat16) * 1.6)(B, Hkv, Sk, Dh)),
            "wq": _w((lambda *s: torch.randn(*s, dtype=torch.bfloat16) * 3.2)(D, Hq * Dh) * (D ** -0.5)),
            "wo": _w((lambda *s: torch.randn(*s, dtype=torch.bfloat16) * 1.6)(Hq * Dh, D) * ((Hq * Dh) ** -0.5)),
        }
    _A_in = _A_setup()

    def _B_setup():
        B, S, D, F = 4, 1, 448, 1792
        return {
            "x": _w((lambda *s: torch.randn(*s, dtype=torch.bfloat16) * 0.05)(B, S, D)),
            "w_gate": _w((lambda *s: torch.randn(*s, dtype=torch.bfloat16) * 0.05)(D, F)),
            "w_up": _w((lambda *s: torch.randn(*s, dtype=torch.bfloat16) * 0.05)(D, F)),
            "w_down": _w((lambda *s: torch.randn(*s, dtype=torch.bfloat16) * 0.05)(F, D)),
        }
    _B_in = _B_setup()

    return {
        "A_x": _A_in["x"],
        "A_k_cache": _A_in["k_cache"],
        "A_v_cache": _A_in["v_cache"],
        "A_wq": _A_in["wq"],
        "A_wo": _A_in["wo"],
        "B_x": _B_in["x"],
        "B_w_gate": _B_in["w_gate"],
        "B_w_up": _B_in["w_up"],
        "B_w_down": _B_in["w_down"],
    }

def reference(A_x, A_k_cache, A_v_cache, A_wq, A_wo, B_x, B_w_gate, B_w_up, B_w_down):
    def _A_ref(x, k_cache, v_cache, wq, wo):
        B, Sq, D = x.shape
        Hq, Dh = 16, 256
        Hkv, Sk = k_cache.shape[1], k_cache.shape[2]
        W = min(4096, max(256, Sk // 4))
        rep = Hq // Hkv
        q = (lambda x, *d: x.permute(*d))((x @ wq).reshape(B, Sq, Hq, Dh), 0, 2, 1, 3)
        k = (lambda x, n, axis: torch.repeat_interleave(x, n, dim=axis))(k_cache[:, :, Sk - W:, :], rep, axis=1)
        v = (lambda x, n, axis: torch.repeat_interleave(x, n, dim=axis))(v_cache[:, :, Sk - W:, :], rep, axis=1)
        scores = torch.einsum("bhqd,bhkd->bhqk", q, k) * (Dh ** -0.5)
        p = _softmax(scores, axis=-1)
        o = torch.einsum("bhqk,bhkd->bhqd", p, v)
        return (lambda x, *d: x.permute(*d))(o, 0, 2, 1, 3).reshape(B, Sq, Hq * Dh) @ wo

    def _B_ref(x, w_gate, w_up, w_down):
        return (_gelu(x @ w_gate) * (x @ w_up)) @ w_down

    x = A_x
    xn = _layernorm(x, axis=-1)
    return x + _A_ref(xn, A_k_cache, A_v_cache, A_wq, A_wo) + _B_ref(xn, B_w_gate, B_w_up, B_w_down)
```

```cpp
#include <cuda_runtime.h>
#include <cuda_bf16.h>
#include <stdint.h>

namespace {

typedef __nv_bfloat16 bf16;

constexpr int DM = 448, HKV = 8, SK = 4096, DH = 256, WIN = 1024, FF = 1792;
constexpr int NCTA = 128;
constexpr int NCW = 16;
constexpr int NCONS = NCW * 32;
constexpr int NTHREADS = NCONS + 32;
constexpr int STAGE = 16384;
constexpr int NSTAGE = 11;
constexpr int INFLIGHT = 4;
constexpr int ROWB = DM * 2;
constexpr uint32_t KEYF = 0xFFF0DEADu;
constexpr uint32_t KEYB = 0xFFADFFADu;
constexpr int SPIN_CAP = 1 << 21;

__device__ uint32_t g_qbox[NCTA][256];
__device__ uint32_t g_sbox[NCTA][4][8];
__device__ uint32_t g_obox[NCTA][16][32];
__device__ uint32_t g_fbox[NCTA][NCTA][32];

constexpr int SM_RING = 0;
constexpr int SM_BAR = NSTAGE * STAGE;
constexpr int SM_XN = SM_BAR + 256;
constexpr int SM_RED = SM_XN + 7168;
constexpr int SM_RES = SM_RED + 16896;
constexpr int SM_Q = SM_RES + 512;
constexpr int SM_SC = SM_Q + 2048;
constexpr int SM_P = SM_SC + 2048;
constexpr int SM_H = SM_P + 2048;
constexpr int SM_O = SM_H + 256;
constexpr int SM_OB = SM_O + 512;
constexpr int SM_ST = SM_OB + 2048;
constexpr int SM_FIN = SM_ST + 32;
constexpr int SM_TOTAL = SM_FIN + 128;

__device__ __forceinline__ float bflo(uint32_t u) { return __uint_as_float(u << 16); }
__device__ __forceinline__ float bfhi(uint32_t u) { return __uint_as_float(u & 0xffff0000u); }
__device__ __forceinline__ float rbf(float x) { return __bfloat162float(__float2bfloat16_rn(x)); }
__device__ __forceinline__ void unpack8(const uint4& u, float (&f)[8]) {
    f[0] = bflo(u.x); f[1] = bfhi(u.x); f[2] = bflo(u.y); f[3] = bfhi(u.y);
    f[4] = bflo(u.z); f[5] = bfhi(u.z); f[6] = bflo(u.w); f[7] = bfhi(u.w);
}
__device__ __forceinline__ uint32_t smem_u32(const void* p) { return (uint32_t)__cvta_generic_to_shared(p); }
__device__ __forceinline__ void mbar_init(uint32_t bar, uint32_t cnt) {
    asm volatile("mbarrier.init.shared::cta.b64 [%0], %1;" :: "r"(bar), "r"(cnt) : "memory");
}
__device__ __forceinline__ void mbar_expect_tx(uint32_t bar, uint32_t bytes) {
    asm volatile("mbarrier.arrive.expect_tx.shared::cta.b64 _, [%0], %1;" :: "r"(bar), "r"(bytes) : "memory");
}
__device__ __forceinline__ void mbar_arrive(uint32_t bar) {
    asm volatile("mbarrier.arrive.shared::cta.b64 _, [%0];" :: "r"(bar) : "memory");
}
__device__ __forceinline__ bool mbar_try_wait(uint32_t bar, uint32_t parity) {
    uint32_t ok;
    asm volatile("{\n.reg .pred p;\nmbarrier.try_wait.parity.shared::cta.b64 p, [%1], %2;\nselp.u32 %0, 1, 0, p;\n}"
                 : "=r"(ok) : "r"(bar), "r"(parity) : "memory");
    return ok;
}
__device__ __forceinline__ void mbar_wait(uint32_t bar, uint32_t parity) {
    int it = 0;
    while (!mbar_try_wait(bar, parity)) { if (++it > SPIN_CAP) break; }
}
__device__ __forceinline__ void bulk_g2s(uint32_t dst, const void* src, uint32_t bytes, uint32_t bar) {
    asm volatile("cp.async.bulk.shared::cluster.global.mbarrier::complete_tx::bytes [%0], [%1], %2, [%3];"
                 :: "r"(dst), "l"(src), "r"(bytes), "r"(bar) : "memory");
}
__device__ __forceinline__ uint32_t ld_poll(const uint32_t* p) {
    uint32_t v; asm volatile("ld.relaxed.gpu.global.u32 %0, [%1];" : "=r"(v) : "l"(p) : "memory"); return v;
}
__device__ __forceinline__ void st_pub(uint32_t* p, uint32_t v) {
    asm volatile("st.relaxed.gpu.global.u32 [%0], %1;" :: "l"(p), "r"(v) : "memory");
}
__device__ __forceinline__ uint32_t poll_word(uint32_t* p) {
    uint32_t v = ld_poll(p);
    int it = 0;
    while (v == 0u) { if (++it > SPIN_CAP) break; v = ld_poll(p); }
    st_pub(p, 0u);
    return v;
}
__device__ __forceinline__ void cons_bar() { asm volatile("bar.sync 1, 512;" ::: "memory"); }
__device__ __forceinline__ float warp_sum(float v) {
#pragma unroll
    for (int o = 16; o > 0; o >>= 1) v += __shfl_xor_sync(0xffffffffu, v, o);
    return v;
}
__device__ __forceinline__ float warp_max(float v) {
#pragma unroll
    for (int o = 16; o > 0; o >>= 1) v = fmaxf(v, __shfl_xor_sync(0xffffffffu, v, o));
    return v;
}
__device__ __forceinline__ uint4 ldg16(const void* p) { return __ldg(reinterpret_cast<const uint4*>(p)); }

__device__ __forceinline__ void gemv32(const uint4 (&wr)[4], const float4* xn4, float* red, int t, int warp, int lane) {
    float a[32];
#pragma unroll
    for (int n = 0; n < 32; n++) a[n] = 0.f;
#pragma unroll
    for (int r = 0; r < 4; r++) {
        const int idx = t + 512 * r;
        if (idx < 1792) {
            const float4 xv = xn4[idx >> 2];
            float f[8]; unpack8(wr[r], f);
#pragma unroll
            for (int e = 0; e < 8; e++) {
                a[e] = fmaf(xv.x, f[e], a[e]);
                a[8 + e] = fmaf(xv.y, f[e], a[8 + e]);
                a[16 + e] = fmaf(xv.z, f[e], a[16 + e]);
                a[24 + e] = fmaf(xv.w, f[e], a[24 + e]);
            }
        }
    }
    float b1[16], b2[8], b3[4];
    const bool h4 = lane & 16, h3 = lane & 8, h2 = lane & 4;
#pragma unroll
    for (int n = 0; n < 16; n++) {
        const float send = h4 ? a[n] : a[n + 16], keep = h4 ? a[n + 16] : a[n];
        b1[n] = keep + __shfl_xor_sync(0xffffffffu, send, 16);
    }
#pragma unroll
    for (int n = 0; n < 8; n++) {
        const float send = h3 ? b1[n] : b1[n + 8], keep = h3 ? b1[n + 8] : b1[n];
        b2[n] = keep + __shfl_xor_sync(0xffffffffu, send, 8);
    }
#pragma unroll
    for (int n = 0; n < 4; n++) {
        const float send = h2 ? b2[n] : b2[n + 4], keep = h2 ? b2[n + 4] : b2[n];
        b3[n] = keep + __shfl_xor_sync(0xffffffffu, send, 4);
    }
    *reinterpret_cast<float4*>(red + warp * 128 + (lane & 3) * 32 + 4 * (lane >> 2)) = make_float4(b3[0], b3[1], b3[2], b3[3]);
}

template <int RPL>
__device__ __forceinline__ void rows_gemv(const unsigned char* blk, const float4* av, int strip, int lane, float (&v8)[8]) {
    const int cl = lane & 7, rgl = lane >> 3;
    const unsigned char* p = blk + (rgl * RPL) * ROWB + (strip * 8 + cl) * 16;
    float a[32];
#pragma unroll
    for (int n = 0; n < 32; n++) a[n] = 0.f;
#pragma unroll
    for (int r = 0; r < RPL; r++) {
        const uint4 u = *reinterpret_cast<const uint4*>(p + r * ROWB);
        const float4 hv = av[rgl * RPL + r];
        float f[8]; unpack8(u, f);
#pragma unroll
        for (int e = 0; e < 8; e++) {
            a[e] = fmaf(hv.x, f[e], a[e]);
            a[8 + e] = fmaf(hv.y, f[e], a[8 + e]);
            a[16 + e] = fmaf(hv.z, f[e], a[16 + e]);
            a[24 + e] = fmaf(hv.w, f[e], a[24 + e]);
        }
    }
    float b1[16];
    const bool h4 = lane & 16, h3 = lane & 8;
#pragma unroll
    for (int n = 0; n < 16; n++) {
        const float send = h4 ? a[n] : a[n + 16], keep = h4 ? a[n + 16] : a[n];
        b1[n] = keep + __shfl_xor_sync(0xffffffffu, send, 16);
    }
#pragma unroll
    for (int n = 0; n < 8; n++) {
        const float send = h3 ? b1[n] : b1[n + 8], keep = h3 ? b1[n + 8] : b1[n];
        v8[n] = keep + __shfl_xor_sync(0xffffffffu, send, 8);
    }
}

__global__ void __launch_bounds__(NTHREADS, 1)
fused_decode_kernel(const bf16* __restrict__ x, const bf16* __restrict__ kc, const bf16* __restrict__ vc,
                    const bf16* __restrict__ wq, const bf16* __restrict__ wo, const bf16* __restrict__ wg,
                    const bf16* __restrict__ wu, const bf16* __restrict__ wd, bf16* __restrict__ out) {
    extern __shared__ __align__(1024) unsigned char smem[];
    unsigned char* ring = smem + SM_RING;
    uint64_t* fullb = reinterpret_cast<uint64_t*>(smem + SM_BAR);
    uint64_t* emptyb = fullb + NSTAGE;
    float* xn_s = reinterpret_cast<float*>(smem + SM_XN);
    float* red = reinterpret_cast<float*>(smem + SM_RED);
    float* res_s = reinterpret_cast<float*>(smem + SM_RES);
    float* q_s = reinterpret_cast<float*>(smem + SM_Q);
    float* sc_s = reinterpret_cast<float*>(smem + SM_SC);
    float* p_s = reinterpret_cast<float*>(smem + SM_P);
    float* h_s = reinterpret_cast<float*>(smem + SM_H);
    float* o_s = reinterpret_cast<float*>(smem + SM_O);
    float* ob_s = reinterpret_cast<float*>(smem + SM_OB);
    float* st_s = reinterpret_cast<float*>(smem + SM_ST);
    float* fin_s = reinterpret_cast<float*>(smem + SM_FIN);

    const int cta = blockIdx.x;
    const int kvh = cta >> 4, b = (cta >> 2) & 3, c = cta & 3;
    const bool ffn = (cta & 7) != 7;
    const int fi = (cta >> 3) * 7 + (cta & 7);
    const int t = threadIdx.x, warp = t >> 5, lane = t & 31;
    const int NITEMS = 16 + (ffn ? 1 : 0) + 2;
    const int IT_WO = 16 + (ffn ? 1 : 0);

    if (t == 0) {
        for (int s = 0; s < NSTAGE; s++) {
            mbar_init(smem_u32(&fullb[s]), 1);
            mbar_init(smem_u32(&emptyb[s]), NCW);
        }
        asm volatile("fence.mbarrier_init.release.cluster;" ::: "memory");
    }
    __syncthreads();

    if (warp == NCW) {
        if (lane == 0) {
            const size_t kvoff = ((size_t)(b * HKV + kvh) * SK + (SK - WIN) + c * 256) * DH;
            const unsigned char* kptr = reinterpret_cast<const unsigned char*>(kc + kvoff);
            const unsigned char* vptr = reinterpret_cast<const unsigned char*>(vc + kvoff);
            const unsigned char* dptr = reinterpret_cast<const unsigned char*>(wd + (size_t)fi * 16 * DM);
            const unsigned char* optr = reinterpret_cast<const unsigned char*>(wo + (size_t)cta * 32 * DM);
            for (int it = 0; it < NITEMS; it++) {
                const int slot = it % NSTAGE;
                const unsigned char* src; uint32_t bytes;
                if (it < 8) { src = kptr + (size_t)it * STAGE; bytes = STAGE; }
                else if (it < 16) { src = vptr + (size_t)(it - 8) * STAGE; bytes = STAGE; }
                else if (it < IT_WO) { src = dptr; bytes = 16 * ROWB; }
                else { src = optr + (size_t)(it - IT_WO) * 16 * ROWB; bytes = 16 * ROWB; }
                if (it >= NSTAGE) mbar_wait(smem_u32(&emptyb[slot]), ((it / NSTAGE) - 1) & 1);
                if (it >= INFLIGHT) { const int j = it - INFLIGHT; mbar_wait(smem_u32(&fullb[j % NSTAGE]), (j / NSTAGE) & 1); }
                mbar_expect_tx(smem_u32(&fullb[slot]), bytes);
                bulk_g2s(smem_u32(ring + slot * STAGE), src, bytes, smem_u32(&fullb[slot]));
            }
        }
        return;
    }

    uint4 wq_r[4], gu_r[4];
#pragma unroll
    for (int r = 0; r < 4; r++) {
        const int idx = t + 512 * r;
        wq_r[r] = make_uint4(0, 0, 0, 0); gu_r[r] = make_uint4(0, 0, 0, 0);
        if (idx < 1792) {
            const int k = idx >> 2, oct = idx & 3;
            wq_r[r] = ldg16(wq + (size_t)k * 4096 + 32 * cta + oct * 8);
        }
    }
    if (ffn) {
#pragma unroll
        for (int r = 0; r < 4; r++) {
            const int idx = t + 512 * r;
            if (idx < 1792) {
                const int k = idx >> 2, oct = idx & 3;
                gu_r[r] = ldg16((oct < 2 ? wg : wu) + (size_t)k * FF + 16 * fi + (oct & 1) * 8);
            }
        }
    }
    float x_res = 0.f;
    if (t < 14) x_res = __bfloat162float(x[cta * 14 + t]);

    if (warp < 4) {
        float xv[14], sum = 0.f;
#pragma unroll
        for (int j = 0; j < 14; j++) { xv[j] = __bfloat162float(x[warp * DM + lane + 32 * j]); sum += xv[j]; }
        sum = warp_sum(sum);
        const float mean = sum / 448.f;
        const float m_bf = rbf(mean);
        float ss = 0.f;
#pragma unroll
        for (int j = 0; j < 14; j++) { const float d = xv[j] - mean; ss = fmaf(d, d, ss); }
        ss = warp_sum(ss);
        const float v_bf = rbf(ss / 448.f);
        const float den = rbf(__fsqrt_rn(rbf(v_bf + 1e-5f)));
#pragma unroll
        for (int j = 0; j < 14; j++) xn_s[(lane + 32 * j) * 4 + warp] = rbf(__fdiv_rn(rbf(xv[j] - m_bf), den));
    }
    cons_bar();
    const float4* xn4 = reinterpret_cast<const float4*>(xn_s);

    gemv32(wq_r, xn4, red, t, warp, lane);
    cons_bar();
    if (t < 128) {
        const int oct = t >> 5, n = t & 31;
        float s = 0.f;
#pragma unroll
        for (int w = 0; w < NCW; w++) s += red[w * 128 + oct * 32 + n];
        res_s[(n >> 3) * 32 + oct * 8 + (n & 7)] = s;
    }
    cons_bar();
    if (t < 256) {
        const int cc = t >> 4, w = t & 15;
        const int bb = cc >> 2;
        __nv_bfloat162 pk = __floats2bfloat162_rn(res_s[bb * 32 + 2 * w], res_s[bb * 32 + 2 * w + 1]);
        st_pub(&g_qbox[kvh * 16 + cc][(cta & 15) * 16 + w], (*reinterpret_cast<uint32_t*>(&pk)) ^ KEYB);
    }

    if (ffn) {
        gemv32(gu_r, xn4, red, t, warp, lane);
        cons_bar();
        if (t < 128) {
            const int oct = t >> 5, n = t & 31;
            float s = 0.f;
#pragma unroll
            for (int w = 0; w < NCW; w++) s += red[w * 128 + oct * 32 + n];
            res_s[(n >> 3) * 32 + oct * 8 + (n & 7)] = s;
        }
        cons_bar();
        if (t < 64) {
            const int bb = t >> 4, f = t & 15;
            const float g = rbf(res_s[bb * 32 + f]), u = rbf(res_s[bb * 32 + 16 + f]);
            const float inner = 0.7978845608028654f * (g + 0.044715f * g * g * g);
            const float gl = rbf(0.5f * g * (1.f + tanhf(inner)));
            h_s[f * 4 + bb] = rbf(gl * u);
        }
    }

    if (t < 256) {
        const uint32_t v = poll_word(&g_qbox[cta][t]) ^ KEYB;
        q_s[2 * t] = bflo(v); q_s[2 * t + 1] = bfhi(v);
    }
    cons_bar();
    float q0[8], q1[8];
    {
        const float4 a0 = *reinterpret_cast<const float4*>(q_s + 8 * lane), a1 = *reinterpret_cast<const float4*>(q_s + 8 * lane + 4);
        const float4 c0 = *reinterpret_cast<const float4*>(q_s + 256 + 8 * lane), c1 = *reinterpret_cast<const float4*>(q_s + 256 + 8 * lane + 4);
        q0[0] = a0.x; q0[1] = a0.y; q0[2] = a0.z; q0[3] = a0.w; q0[4] = a1.x; q0[5] = a1.y; q0[6] = a1.z; q0[7] = a1.w;
        q1[0] = c0.x; q1[1] = c0.y; q1[2] = c0.z; q1[3] = c0.w; q1[4] = c1.x; q1[5] = c1.y; q1[6] = c1.z; q1[7] = c1.w;
    }

#pragma unroll 1
    for (int s = 0; s < 8; s++) {
        const int slot = s % NSTAGE;
        mbar_wait(smem_u32(&fullb[slot]), (s / NSTAGE) & 1);
        const uint4* sp = reinterpret_cast<const uint4*>(ring + slot * STAGE);
        const uint4 u0 = sp[(2 * warp) * 32 + lane], u1 = sp[(2 * warp + 1) * 32 + lane];
        float f[8];
        float d00 = 0.f, d01 = 0.f, d10 = 0.f, d11 = 0.f;
        unpack8(u0, f);
#pragma unroll
        for (int e = 0; e < 8; e++) { d00 = fmaf(f[e], q0[e], d00); d01 = fmaf(f[e], q1[e], d01); }
        unpack8(u1, f);
#pragma unroll
        for (int e = 0; e < 8; e++) { d10 = fmaf(f[e], q0[e], d10); d11 = fmaf(f[e], q1[e], d11); }
        const bool h4 = lane & 16, h3 = lane & 8;
        float e0 = (h4 ? d10 : d00) + __shfl_xor_sync(0xffffffffu, h4 ? d00 : d10, 16);
        float e1 = (h4 ? d11 : d01) + __shfl_xor_sync(0xffffffffu, h4 ? d01 : d11, 16);
        float g = (h3 ? e1 : e0) + __shfl_xor_sync(0xffffffffu, h3 ? e0 : e1, 8);
        g += __shfl_xor_sync(0xffffffffu, g, 4);
        g += __shfl_xor_sync(0xffffffffu, g, 2);
        g += __shfl_xor_sync(0xffffffffu, g, 1);
        if ((lane & 7) == 0) sc_s[(h3 ? 256 : 0) + s * 32 + 2 * warp + (h4 ? 1 : 0)] = rbf(g) * 0.0625f;
        __syncwarp();
        if (lane == 0) mbar_arrive(smem_u32(&emptyb[slot]));
    }
    cons_bar();

    if (warp == 0) {
        const float4 a0 = *reinterpret_cast<const float4*>(sc_s + 8 * lane), a1 = *reinterpret_cast<const float4*>(sc_s + 8 * lane + 4);
        const float4 c0 = *reinterpret_cast<const float4*>(sc_s + 256 + 8 * lane), c1 = *reinterpret_cast<const float4*>(sc_s + 256 + 8 * lane + 4);
        float m0 = fmaxf(fmaxf(fmaxf(a0.x, a0.y), fmaxf(a0.z, a0.w)), fmaxf(fmaxf(a1.x, a1.y), fmaxf(a1.z, a1.w)));
        float m1 = fmaxf(fmaxf(fmaxf(c0.x, c0.y), fmaxf(c0.z, c0.w)), fmaxf(fmaxf(c1.x, c1.y), fmaxf(c1.z, c1.w)));
        m0 = warp_max(m0); m1 = warp_max(m1);
        float l0 = expf(a0.x - m0) + expf(a0.y - m0) + expf(a0.z - m0) + expf(a0.w - m0) + expf(a1.x - m0) + expf(a1.y - m0) + expf(a1.z - m0) + expf(a1.w - m0);
        float l1 = expf(c0.x - m1) + expf(c0.y - m1) + expf(c0.z - m1) + expf(c0.w - m1) + expf(c1.x - m1) + expf(c1.y - m1) + expf(c1.z - m1) + expf(c1.w - m1);
        l0 = warp_sum(l0); l1 = warp_sum(l1);
        {
            const int w = lane & 7;
            const float v = (w == 0) ? m0 : (w == 1) ? l0 : (w == 2) ? m1 : (w == 3) ? l1 : 1.0f;
            st_pub(&g_sbox[(cta & ~3) + (lane >> 3)][c][w], __float_as_uint(v) ^ KEYF);
        }
        float mine = 0.f;
        if (lane < 16) mine = __uint_as_float(poll_word(&g_sbox[cta][lane >> 2][lane & 3]) ^ KEYF);
        __syncwarp();
        float M0 = -INFINITY, M1 = -INFINITY;
#pragma unroll
        for (int cc = 0; cc < 4; cc++) {
            M0 = fmaxf(M0, __shfl_sync(0xffffffffu, mine, cc * 4 + 0));
            M1 = fmaxf(M1, __shfl_sync(0xffffffffu, mine, cc * 4 + 2));
        }
        float L0 = 0.f, L1 = 0.f;
#pragma unroll
        for (int cc = 0; cc < 4; cc++) {
            const float mc0 = __shfl_sync(0xffffffffu, mine, cc * 4 + 0), lc0 = __shfl_sync(0xffffffffu, mine, cc * 4 + 1);
            const float mc1 = __shfl_sync(0xffffffffu, mine, cc * 4 + 2), lc1 = __shfl_sync(0xffffffffu, mine, cc * 4 + 3);
            L0 += lc0 * expf(mc0 - M0);
            L1 += lc1 * expf(mc1 - M1);
        }
        if (lane == 0) { st_s[0] = M0; st_s[1] = L0; st_s[2] = M1; st_s[3] = L1; }
    }
    cons_bar();
    {
        const int h = t >> 8, key = t & 255;
        const float M = st_s[2 * h], L = st_s[2 * h + 1];
        p_s[key * 2 + h] = rbf(__fdiv_rn(expf(sc_s[h * 256 + key] - M), L));
    }
    cons_bar();

    {
        const int dq = warp & 3, kg = warp >> 2, g8 = lane >> 3, j = lane & 7;
        const float2* p2 = reinterpret_cast<const float2*>(p_s);
        float acc0[8], acc1[8];
#pragma unroll
        for (int e = 0; e < 8; e++) { acc0[e] = 0.f; acc1[e] = 0.f; }
#pragma unroll 1
        for (int s = 0; s < 8; s++) {
            const int it = 8 + s, slot = it % NSTAGE;
            mbar_wait(smem_u32(&fullb[slot]), (it / NSTAGE) & 1);
            const unsigned char* stg = ring + slot * STAGE;
#pragma unroll
            for (int i2 = 0; i2 < 2; i2++) {
                const int key = kg * 8 + i2 * 4 + g8;
                const uint4 u = *reinterpret_cast<const uint4*>(stg + key * 512 + dq * 128 + j * 16);
                const float2 pp = p2[s * 32 + key];
                float f[8]; unpack8(u, f);
#pragma unroll
                for (int e = 0; e < 8; e++) { acc0[e] = fmaf(pp.x, f[e], acc0[e]); acc1[e] = fmaf(pp.y, f[e], acc1[e]); }
            }
            __syncwarp();
            if (lane == 0) mbar_arrive(smem_u32(&emptyb[slot]));
        }
        const bool h4 = lane & 16, h3 = lane & 8;
        float cc8[8], c4[4];
#pragma unroll
        for (int e = 0; e < 8; e++) cc8[e] = (h4 ? acc1[e] : acc0[e]) + __shfl_xor_sync(0xffffffffu, h4 ? acc0[e] : acc1[e], 16);
#pragma unroll
        for (int n = 0; n < 4; n++) c4[n] = (h3 ? cc8[n + 4] : cc8[n]) + __shfl_xor_sync(0xffffffffu, h3 ? cc8[n] : cc8[n + 4], 8);
        *reinterpret_cast<float4*>(red + kg * 512 + (h4 ? 256 : 0) + dq * 64 + j * 8 + (h3 ? 4 : 0)) = make_float4(c4[0], c4[1], c4[2], c4[3]);
    }
    cons_bar();
    {
        const int h = t >> 8, d = t & 255;
        const float v = ((red[h * 256 + d] + red[512 + h * 256 + d]) + red[1024 + h * 256 + d]) + red[1536 + h * 256 + d];
        st_pub(&g_obox[kvh * 16 + h * 8 + (d >> 5)][b * 4 + c][d & 31], __float_as_uint(v) ^ KEYF);
    }
    cons_bar();

    const int strip = warp % 7, half = warp / 7;
    if (ffn) {
        const int it = 16, slot = it % NSTAGE;
        mbar_wait(smem_u32(&fullb[slot]), (it / NSTAGE) & 1);
        if (half < 2) {
            float v8[8];
            rows_gemv<2>(ring + slot * STAGE + half * 8 * ROWB, reinterpret_cast<const float4*>(h_s) + half * 8, strip, lane, v8);
            float* dst = red + half * 1792 + (lane >> 3) * DM + (strip * 8 + (lane & 7)) * 8;
            *reinterpret_cast<float4*>(dst) = make_float4(v8[0], v8[1], v8[2], v8[3]);
            *reinterpret_cast<float4*>(dst + 4) = make_float4(v8[4], v8[5], v8[6], v8[7]);
        }
        cons_bar();
#pragma unroll
        for (int r = 0; r < 4; r++) {
            const int ep = t + 512 * r, j = ep >> 4, w = ep & 15;
            const float v = (w < 14) ? red[14 * j + w] + red[1792 + 14 * j + w] : 1.0f;
            st_pub(&g_fbox[j][cta][16 + w], __float_as_uint(v) ^ KEYF);
        }
        cons_bar();
    }

    ob_s[t] = __uint_as_float(poll_word(&g_obox[cta][t >> 5][t & 31]) ^ KEYF);
    cons_bar();
    if (t < 128) {
        const int bb = t >> 5, d = t & 31;
        const float v = ((ob_s[(bb * 4 + 0) * 32 + d] + ob_s[(bb * 4 + 1) * 32 + d]) + ob_s[(bb * 4 + 2) * 32 + d]) + ob_s[(bb * 4 + 3) * 32 + d];
        o_s[d * 4 + bb] = rbf(v);
    }
    cons_bar();

    if (half < 2) {
        const int it = IT_WO + half, slot = it % NSTAGE;
        mbar_wait(smem_u32(&fullb[slot]), (it / NSTAGE) & 1);
        float v8[8];
        rows_gemv<4>(ring + slot * STAGE, reinterpret_cast<const float4*>(o_s) + half * 16, strip, lane, v8);
        float* dst = red + half * 1792 + (lane >> 3) * DM + (strip * 8 + (lane & 7)) * 8;
        *reinterpret_cast<float4*>(dst) = make_float4(v8[0], v8[1], v8[2], v8[3]);
        *reinterpret_cast<float4*>(dst + 4) = make_float4(v8[4], v8[5], v8[6], v8[7]);
    }
    cons_bar();
#pragma unroll
    for (int r = 0; r < 4; r++) {
        const int ep = t + 512 * r, j = ep >> 4, w = ep & 15;
        const float v = (w < 14) ? red[14 * j + w] + red[1792 + 14 * j + w] : 1.0f;
        st_pub(&g_fbox[j][cta][w], __float_as_uint(v) ^ KEYF);
    }

    {
        uint32_t* fb = &g_fbox[cta][0][0];
        uint32_t v[8];
        bool need[8];
#pragma unroll
        for (int r = 0; r < 8; r++) {
            const int widx = t + 512 * r, pi = widx >> 5, w = widx & 31;
            need[r] = (w < 14) || (w >= 16 && w < 30 && (pi & 7) != 7);
            v[r] = need[r] ? ld_poll(fb + widx) : 1u;
        }
        int itc = 0;
        bool pending;
        do {
            pending = false;
#pragma unroll
            for (int r = 0; r < 8; r++) {
                if (v[r] == 0u) { v[r] = ld_poll(fb + t + 512 * r); pending |= (v[r] == 0u); }
            }
        } while (pending && ++itc < SPIN_CAP);
        cons_bar();
#pragma unroll
        for (int r = 0; r < 8; r++) {
            const int widx = t + 512 * r, pi = widx >> 5, w = widx & 31;
            red[pi * 33 + w] = need[r] ? __uint_as_float(v[r] ^ KEYF) : 0.f;
            st_pub(fb + widx, 0u);
        }
    }
    cons_bar();
    if (t < 448) {
        const int o = t >> 4, part = t & 15;
        const int w = (o < 14) ? o : o + 2;
        float s = 0.f;
#pragma unroll
        for (int m = 0; m < 8; m++) s += red[(m * 16 + part) * 33 + w];
        s += __shfl_xor_sync(0xffffffffu, s, 8);
        s += __shfl_xor_sync(0xffffffffu, s, 4);
        s += __shfl_xor_sync(0xffffffffu, s, 2);
        s += __shfl_xor_sync(0xffffffffu, s, 1);
        if (part == 0) fin_s[o] = s;
    }
    cons_bar();
    if (t < 14) {
        const float A = rbf(fin_s[t]), Bv = rbf(fin_s[14 + t]);
        out[cta * 14 + t] = __float2bfloat16_rn(rbf(x_res + A) + Bv);
    }
}

}

extern "C" void kernel_launch(void* const* d_in, const int* in_sizes, int n_in, void* d_out, int out_size) {
    (void)in_sizes; (void)n_in; (void)out_size;
    const bf16* x = (const bf16*)d_in[0];
    const bf16* kc = (const bf16*)d_in[1];
    const bf16* vc = (const bf16*)d_in[2];
    const bf16* wq = (const bf16*)d_in[3];
    const bf16* wo = (const bf16*)d_in[4];
    const bf16* wg = (const bf16*)d_in[6];
    const bf16* wu = (const bf16*)d_in[7];
    const bf16* wd = (const bf16*)d_in[8];
    bf16* out = (bf16*)d_out;
    cudaFuncSetAttribute(fused_decode_kernel, cudaFuncAttributeMaxDynamicSharedMemorySize, SM_TOTAL);
    fused_decode_kernel<<<NCTA, NTHREADS, SM_TOTAL>>>(x, kc, vc, wq, wo, wg, wu, wd, out);
}
```

```cpp
#include <cuda_runtime.h>
#include <cuda_bf16.h>
#include <cuda.h>
#include <stdint.h>

namespace {

typedef __nv_bfloat16 bf16;

constexpr int DM = 448, HKV = 8, SK = 4096, DH = 256, WIN = 1024, FF = 1792;
constexpr int NCTA = 128;
constexpr int NCW = 16;
constexpr int NCONS = NCW * 32;
constexpr int NTHREADS = NCONS + 32;
constexpr int STAGE = 16384;
constexpr int NSTAGE = 12;
#define INFLIGHT_ITEMS 4
constexpr int INFLIGHT = INFLIGHT_ITEMS;
#define FRONT_K_ITEMS 1
constexpr uint32_t KEYF = 0xFFF0DEADu;
constexpr uint32_t KEYB = 0xFFADFFADu;
constexpr int SPIN_CAP = 1 << 21;

__device__ uint32_t g_qbox[NCTA][256];
__device__ uint32_t g_sbox[NCTA][4][2][8];
__device__ uint32_t g_obox[NCTA][16][32];
__device__ uint32_t g_fbox[NCTA][NCTA][32];

#define PROF(n) do { } while (0)

constexpr int XN_PITCH = 456, QP_PITCH = 264, H_PITCH = 24, O_PITCH = 40;
constexpr int SM_RING = 0;
constexpr int SM_BAR = NSTAGE * STAGE;
constexpr int SM_XN = SM_BAR + 256;
constexpr int SM_RED = SM_XN + 4 * XN_PITCH * 2;
constexpr int SM_Q = SM_RED + 8192;
constexpr int SM_P = SM_Q + 2 * QP_PITCH * 2;
constexpr int SM_SC = SM_P + 2 * QP_PITCH * 2;
constexpr int SM_H = SM_SC + 2048;
constexpr int SM_O = SM_H + 4 * H_PITCH * 2;
constexpr int SM_ST = SM_O + 4 * O_PITCH * 2;
constexpr int SM_FIN = SM_ST + 32;
constexpr int SM_TOTAL = SM_FIN + 128;
static_assert(SM_TOTAL <= 232448, "smem");

__device__ __forceinline__ float rbf(float x) { return __bfloat162float(__float2bfloat16_rn(x)); }
__device__ __forceinline__ uint32_t smem_u32(const void* p) { return (uint32_t)__cvta_generic_to_shared(p); }
__device__ __forceinline__ void mbar_init(uint32_t bar, uint32_t cnt) {
    asm volatile("mbarrier.init.shared::cta.b64 [%0], %1;" :: "r"(bar), "r"(cnt) : "memory");
}
__device__ __forceinline__ void mbar_expect_tx(uint32_t bar, uint32_t bytes) {
    asm volatile("mbarrier.arrive.expect_tx.shared::cta.b64 _, [%0], %1;" :: "r"(bar), "r"(bytes) : "memory");
}
__device__ __forceinline__ void mbar_arrive(uint32_t bar) {
    asm volatile("mbarrier.arrive.shared::cta.b64 _, [%0];" :: "r"(bar) : "memory");
}
__device__ __forceinline__ bool mbar_try_wait(uint32_t bar, uint32_t parity) {
    uint32_t ok;
    asm volatile("{\n.reg .pred p;\nmbarrier.try_wait.parity.shared::cta.b64 p, [%1], %2;\nselp.u32 %0, 1, 0, p;\n}"
                 : "=r"(ok) : "r"(bar), "r"(parity) : "memory");
    return ok;
}
__device__ __forceinline__ void mbar_wait(uint32_t bar, uint32_t parity) {
    int it = 0;
    while (!mbar_try_wait(bar, parity)) { if (++it > SPIN_CAP) break; }
}
__device__ __forceinline__ void tma2d(uint32_t dst, const CUtensorMap* tm, int c0, int c1, uint32_t bar) {
    asm volatile("cp.async.bulk.tensor.2d.shared::cluster.global.mbarrier::complete_tx::bytes [%0], [%1, {%2, %3}], [%4];"
                 :: "r"(dst), "l"(tm), "r"(c0), "r"(c1), "r"(bar) : "memory");
}
__device__ __forceinline__ uint32_t ld_poll(const uint32_t* p) {
    uint32_t v; asm volatile("ld.relaxed.gpu.global.u32 %0, [%1];" : "=r"(v) : "l"(p) : "memory"); return v;
}
__device__ __forceinline__ void st_pub(uint32_t* p, uint32_t v) {
    asm volatile("st.relaxed.gpu.global.u32 [%0], %1;" :: "l"(p), "r"(v) : "memory");
}
__device__ __forceinline__ void st_pub2(uint32_t* p, uint32_t v0, uint32_t v1) {
    asm volatile("st.relaxed.gpu.global.v2.u32 [%0], {%1, %2};" :: "l"(p), "r"(v0), "r"(v1) : "memory");
}
__device__ __forceinline__ uint32_t poll_word(uint32_t* p) {
    uint32_t v = ld_poll(p);
    int it = 0;
    while (v == 0u) { if (++it > SPIN_CAP) break; v = ld_poll(p); }
    st_pub(p, 0u);
    return v;
}
__device__ __forceinline__ void cons_bar() { asm volatile("bar.sync 1, 512;" ::: "memory"); }
__device__ __forceinline__ float warp_sum(float v) {
#pragma unroll
    for (int o = 16; o > 0; o >>= 1) v += __shfl_xor_sync(0xffffffffu, v, o);
    return v;
}
__device__ __forceinline__ float warp_max(float v) {
#pragma unroll
    for (int o = 16; o > 0; o >>= 1) v = fmaxf(v, __shfl_xor_sync(0xffffffffu, v, o));
    return v;
}
__device__ __forceinline__ uint32_t lds32(uint32_t addr) {
    uint32_t v; asm volatile("ld.shared.b32 %0, [%1];" : "=r"(v) : "r"(addr)); return v;
}
__device__ __forceinline__ void ldsm_x4(uint32_t addr, uint32_t& r0, uint32_t& r1, uint32_t& r2, uint32_t& r3) {
    asm volatile("ldmatrix.sync.aligned.m8n8.x4.shared.b16 {%0,%1,%2,%3}, [%4];"
                 : "=r"(r0), "=r"(r1), "=r"(r2), "=r"(r3) : "r"(addr) : "memory");
}
__device__ __forceinline__ void ldsm_x4_t(uint32_t addr, uint32_t& r0, uint32_t& r1, uint32_t& r2, uint32_t& r3) {
    asm volatile("ldmatrix.sync.aligned.m8n8.x4.trans.shared.b16 {%0,%1,%2,%3}, [%4];"
                 : "=r"(r0), "=r"(r1), "=r"(r2), "=r"(r3) : "r"(addr) : "memory");
}
__device__ __forceinline__ void mma_bf16(float (&c)[4], uint32_t a0, uint32_t a2, uint32_t b0, uint32_t b1) {
    asm volatile("mma.sync.aligned.m16n8k16.row.col.f32.bf16.bf16.f32 {%0,%1,%2,%3}, {%4,%5,%6,%7}, {%8,%9}, {%0,%1,%2,%3};"
                 : "+f"(c[0]), "+f"(c[1]), "+f"(c[2]), "+f"(c[3])
                 : "r"(a0), "r"(0u), "r"(a2), "r"(0u), "r"(b0), "r"(b1));
}

struct Maps { CUtensorMap k, v, wq, wg, wu, wd, wo; };

__global__ void __launch_bounds__(NTHREADS, 1)
fused_decode_kernel(const __grid_constant__ Maps tm, const bf16* __restrict__ x, bf16* __restrict__ out) {
    extern __shared__ __align__(1024) unsigned char smem[];
    const uint32_t ring = smem_u32(smem + SM_RING);
    uint64_t* fullb = reinterpret_cast<uint64_t*>(smem + SM_BAR);
    uint64_t* emptyb = fullb + NSTAGE;
    bf16* xn_bf = reinterpret_cast<bf16*>(smem + SM_XN);
    float* red = reinterpret_cast<float*>(smem + SM_RED);
    bf16* q_bf = reinterpret_cast<bf16*>(smem + SM_Q);
    bf16* p_bf = reinterpret_cast<bf16*>(smem + SM_P);
    float* sc_s = reinterpret_cast<float*>(smem + SM_SC);
    bf16* h_bf = reinterpret_cast<bf16*>(smem + SM_H);
    bf16* o_bf = reinterpret_cast<bf16*>(smem + SM_O);
    float* st_s = reinterpret_cast<float*>(smem + SM_ST);
    float* fin_s = reinterpret_cast<float*>(smem + SM_FIN);

    const int cta = blockIdx.x;
    const int kvh = cta >> 4, b = (cta >> 2) & 3, c = cta & 3;
    const bool ffn = (cta & 7) != 7;
    const int fi = (cta >> 3) * 7 + (cta & 7);
    const int t = threadIdx.x, warp = t >> 5, lane = t & 31;
    const int g = lane >> 2, tq = lane & 3;
    const int IT_WO = 18 + (ffn ? 3 : 0);
    const int NITEMS = IT_WO + 2;

    if (t == 0) {
        for (int s = 0; s < NSTAGE; s++) {
            mbar_init(smem_u32(&fullb[s]), 1);
            mbar_init(smem_u32(&emptyb[s]), NCW);
        }
        asm volatile("fence.mbarrier_init.release.cluster;" ::: "memory");
    }
    __syncthreads();

    if (warp == NCW) {
        if (lane == 0) {
            const int kvrow = (b * HKV + kvh) * SK + (SK - WIN) + c * 256;
            for (int it = 0; it < NITEMS; it++) {
                const int slot = it % NSTAGE;
                const uint32_t dst = ring + slot * STAGE, fb = smem_u32(&fullb[slot]);
                if (it >= NSTAGE) mbar_wait(smem_u32(&emptyb[slot]), ((it / NSTAGE) - 1) & 1);
                if (it >= INFLIGHT) { const int j = it - INFLIGHT; mbar_wait(smem_u32(&fullb[j % NSTAGE]), (j / NSTAGE) & 1); }
                if (it == 2 + FRONT_K_ITEMS) mbar_wait(smem_u32(&fullb[1]), 0);
                if (it < 2) {
                    mbar_expect_tx(fb, 224 * 64);
                    tma2d(dst, &tm.wq, 32 * cta, 224 * it, fb);
                } else if (it < 18) {
                    const CUtensorMap* m = it < 10 ? &tm.k : &tm.v;
                    const int row = kvrow + ((it - 2) & 7) * 32;
                    mbar_expect_tx(fb, STAGE);
#pragma unroll
                    for (int j = 0; j < 4; j++) tma2d(dst + j * 4096, m, 64 * j, row, fb);
                } else if (it < IT_WO) {
                    if (it < 20) {
                        const CUtensorMap* m = it == 18 ? &tm.wg : &tm.wu;
                        mbar_expect_tx(fb, 2 * 224 * 32);
                        tma2d(dst, m, 16 * fi, 0, fb);
                        tma2d(dst + 7168, m, 16 * fi, 224, fb);
                    } else {
                        mbar_expect_tx(fb, 7 * 2048);
#pragma unroll
                        for (int j = 0; j < 7; j++) tma2d(dst + j * 2048, &tm.wd, 64 * j, 16 * fi, fb);
                    }
                } else {
                    const int j0 = (it - IT_WO) * 4, nj = (it == IT_WO) ? 4 : 3;
                    mbar_expect_tx(fb, nj * 4096);
                    for (int j = 0; j < nj; j++) tma2d(dst + j * 4096, &tm.wo, 64 * (j0 + j), 32 * cta, fb);
                }
            }
        }
        return;
    }

    PROF(0);
    float x_res = 0.f;
    if (t < 14) x_res = __bfloat162float(x[cta * 14 + t]);

    if (warp < 4) {
        float xv[14], sum = 0.f;
#pragma unroll
        for (int j = 0; j < 14; j++) { xv[j] = __bfloat162float(x[warp * DM + lane + 32 * j]); sum += xv[j]; }
        sum = warp_sum(sum);
        const float mean = sum / 448.f;
        const float m_bf = rbf(mean);
        float ss = 0.f;
#pragma unroll
        for (int j = 0; j < 14; j++) { const float d = xv[j] - mean; ss = fmaf(d, d, ss); }
        ss = warp_sum(ss);
        const float v_bf = rbf(ss / 448.f);
        const float den = rbf(__fsqrt_rn(rbf(v_bf + 1e-5f)));
#pragma unroll
        for (int j = 0; j < 14; j++) xn_bf[warp * XN_PITCH + lane + 32 * j] = __float2bfloat16_rn(__fdiv_rn(rbf(xv[j] - m_bf), den));
    }
    cons_bar();
    PROF(1);
    const uint32_t xn_u = smem_u32(xn_bf);

    mbar_wait(smem_u32(&fullb[0]), 0);
    mbar_wait(smem_u32(&fullb[1]), 0);
    if (warp < 14) {
        const int box = warp / 7, kk = warp % 7;
        const uint32_t base = ring + box * STAGE;
        float cc[4][4];
#pragma unroll
        for (int n = 0; n < 4; n++) { cc[n][0] = cc[n][1] = cc[n][2] = cc[n][3] = 0.f; }
#pragma unroll
        for (int i = 0; i < 2; i++) {
            const int ks = 2 * kk + i, kgl = box * 224 + ks * 16;
            uint32_t a0 = 0, a2 = 0;
            if (g < 4) { a0 = lds32(xn_u + (g * XN_PITCH + kgl + 2 * tq) * 2); a2 = lds32(xn_u + (g * XN_PITCH + kgl + 8 + 2 * tq) * 2); }
            const int r = ks * 16 + (lane & 7) + ((lane >> 3) & 1) * 8;
#pragma unroll
            for (int cp = 0; cp < 2; cp++) {
                const int ch = 2 * cp + (lane >> 4);
                uint32_t b0, b1, b2, b3;
                ldsm_x4_t(base + r * 64 + ((ch ^ ((r >> 1) & 3)) << 4), b0, b1, b2, b3);
                mma_bf16(cc[2 * cp], a0, a2, b0, b1);
                mma_bf16(cc[2 * cp + 1], a0, a2, b2, b3);
            }
        }
        if (lane < 16) {
#pragma unroll
            for (int n = 0; n < 4; n++) *reinterpret_cast<float2*>(red + (warp * 4 + g) * 32 + n * 8 + 2 * tq) = make_float2(cc[n][0], cc[n][1]);
        }
    }
    __syncwarp();
    if (lane == 0) { mbar_arrive(smem_u32(&emptyb[0])); mbar_arrive(smem_u32(&emptyb[1])); }
    cons_bar();
    if (t < 128) {
        const int bb = t >> 5, col = t & 31;
        float s = 0.f;
#pragma unroll
        for (int w = 0; w < 14; w++) s += red[(w * 4 + bb) * 32 + col];
        const float s2 = __shfl_down_sync(0xffffffffu, s, 1);
        if ((col & 1) == 0) {
            __nv_bfloat162 pk = __floats2bfloat162_rn(s, s2);
            const uint32_t wv = (*reinterpret_cast<uint32_t*>(&pk)) ^ KEYB;
#pragma unroll
            for (int cc2 = 0; cc2 < 4; cc2++) st_pub(&g_qbox[kvh * 16 + bb * 4 + cc2][(cta & 15) * 16 + (col >> 1)], wv);
        }
    }
    PROF(2);

    if (t < 256) {
        const uint32_t v = poll_word(&g_qbox[cta][t]) ^ KEYB;
        *reinterpret_cast<uint32_t*>(q_bf + (t >> 7) * QP_PITCH + 2 * (t & 127)) = v;
    }
    cons_bar();
    PROF(3);

    {
        const uint32_t q_u = smem_u32(q_bf);
        const int nt = warp & 3, kq = warp >> 2;
        uint32_t qa[4][2];
#pragma unroll
        for (int ks = 0; ks < 4; ks++) {
            qa[ks][0] = 0; qa[ks][1] = 0;
            if (g < 2) { qa[ks][0] = lds32(q_u + (g * QP_PITCH + kq * 64 + ks * 16 + 2 * tq) * 2); qa[ks][1] = lds32(q_u + (g * QP_PITCH + kq * 64 + ks * 16 + 8 + 2 * tq) * 2); }
        }
        const int row = nt * 8 + (lane & 7);
#pragma unroll 1
        for (int s = 0; s < 8; s++) {
            const int it = 2 + s, slot = it % NSTAGE;
            mbar_wait(smem_u32(&fullb[slot]), (it / NSTAGE) & 1);
            const uint32_t bb = ring + slot * STAGE + kq * 4096 + row * 128;
            float cc[4] = {0.f, 0.f, 0.f, 0.f};
#pragma unroll
            for (int i = 0; i < 2; i++) {
                const int ch = 4 * i + (lane >> 3);
                uint32_t r0, r1, r2, r3;
                ldsm_x4(bb + ((ch ^ (lane & 7)) << 4), r0, r1, r2, r3);
                mma_bf16(cc, qa[2 * i][0], qa[2 * i][1], r0, r1);
                mma_bf16(cc, qa[2 * i + 1][0], qa[2 * i + 1][1], r2, r3);
            }
            if (lane < 8) *reinterpret_cast<float2*>(red + (kq * 2 + g) * 256 + s * 32 + nt * 8 + 2 * tq) = make_float2(cc[0], cc[1]);
            __syncwarp();
            if (lane == 0) mbar_arrive(smem_u32(&emptyb[slot]));
        }
    }
    cons_bar();
    PROF(4);

    if (warp < 2) {
        const int h = warp;
        float sv[8];
#pragma unroll
        for (int half = 0; half < 2; half++) {
            float4 a = *reinterpret_cast<const float4*>(red + (0 * 2 + h) * 256 + lane * 8 + half * 4);
#pragma unroll
            for (int kq = 1; kq < 4; kq++) {
                const float4 v = *reinterpret_cast<const float4*>(red + (kq * 2 + h) * 256 + lane * 8 + half * 4);
                a.x += v.x; a.y += v.y; a.z += v.z; a.w += v.w;
            }
            sv[half * 4 + 0] = rbf(a.x) * 0.0625f; sv[half * 4 + 1] = rbf(a.y) * 0.0625f;
            sv[half * 4 + 2] = rbf(a.z) * 0.0625f; sv[half * 4 + 3] = rbf(a.w) * 0.0625f;
            *reinterpret_cast<float4*>(sc_s + h * 256 + lane * 8 + half * 4) = make_float4(sv[half * 4], sv[half * 4 + 1], sv[half * 4 + 2], sv[half * 4 + 3]);
        }
        float m = sv[0];
#pragma unroll
        for (int j = 1; j < 8; j++) m = fmaxf(m, sv[j]);
        m = warp_max(m);
        float l = 0.f;
#pragma unroll
        for (int j = 0; j < 8; j++) l += expf(sv[j] - m);
        l = warp_sum(l);
        {
            const int w = lane & 7;
            const float v = (w == 0) ? m : (w == 1) ? l : 1.0f;
            st_pub(&g_sbox[(cta & ~3) + (lane >> 3)][c][h][w], __float_as_uint(v) ^ KEYF);
        }
        float mine = 0.f;
        if (lane < 8) mine = __uint_as_float(poll_word(&g_sbox[cta][lane >> 1][h][lane & 1]) ^ KEYF);
        __syncwarp();
        float M = -INFINITY;
#pragma unroll
        for (int cc = 0; cc < 4; cc++) M = fmaxf(M, __shfl_sync(0xffffffffu, mine, cc * 2));
        float L = 0.f;
#pragma unroll
        for (int cc = 0; cc < 4; cc++) L += __shfl_sync(0xffffffffu, mine, cc * 2 + 1) * expf(__shfl_sync(0xffffffffu, mine, cc * 2) - M);
        if (lane == 0) { st_s[2 * h] = M; st_s[2 * h + 1] = L; }
    }
    cons_bar();
    {
        const int h = t >> 8, key = t & 255;
        p_bf[h * QP_PITCH + key] = __float2bfloat16_rn(__fdiv_rn(expf(sc_s[h * 256 + key] - st_s[2 * h]), st_s[2 * h + 1]));
    }
    cons_bar();
    PROF(5);

    {
        const uint32_t p_u = smem_u32(p_bf);
        const int jb = warp >> 2, cb = (warp & 3) * 2;
        float acc[2][4];
#pragma unroll
        for (int n = 0; n < 2; n++) { acc[n][0] = acc[n][1] = acc[n][2] = acc[n][3] = 0.f; }
        const int rl = (lane & 7) + ((lane >> 3) & 1) * 8, ch = cb + (lane >> 4);
#pragma unroll 1
        for (int s = 0; s < 8; s++) {
            const int it = 10 + s, slot = it % NSTAGE;
            mbar_wait(smem_u32(&fullb[slot]), (it / NSTAGE) & 1);
            const uint32_t bb = ring + slot * STAGE + jb * 4096;
#pragma unroll
            for (int ks = 0; ks < 2; ks++) {
                uint32_t a0 = 0, a2 = 0;
                if (g < 2) { const int k0 = s * 32 + ks * 16; a0 = lds32(p_u + (g * QP_PITCH + k0 + 2 * tq) * 2); a2 = lds32(p_u + (g * QP_PITCH + k0 + 8 + 2 * tq) * 2); }
                const int r = ks * 16 + rl;
                uint32_t r0, r1, r2, r3;
                ldsm_x4_t(bb + r * 128 + ((ch ^ (r & 7)) << 4), r0, r1, r2, r3);
                mma_bf16(acc[0], a0, a2, r0, r1);
                mma_bf16(acc[1], a0, a2, r2, r3);
            }
            __syncwarp();
            if (lane == 0) mbar_arrive(smem_u32(&emptyb[slot]));
        }
        if (lane < 8) {
            uint32_t* dst = &g_obox[kvh * 16 + g * 8 + (warp >> 1)][b * 4 + c][(warp & 1) * 16 + 2 * tq];
            st_pub2(dst, __float_as_uint(acc[0][0]) ^ KEYF, __float_as_uint(acc[0][1]) ^ KEYF);
            st_pub2(dst + 8, __float_as_uint(acc[1][0]) ^ KEYF, __float_as_uint(acc[1][1]) ^ KEYF);
        }
    }
    PROF(6);

    if (ffn) {
        const int sg = 18 % NSTAGE, su = 19 % NSTAGE, sd = 20 % NSTAGE;
        mbar_wait(smem_u32(&fullb[sg]), (18 / NSTAGE) & 1);
        mbar_wait(smem_u32(&fullb[su]), (19 / NSTAGE) & 1);
        if (warp < 14) {
            const int box = warp / 7, kk = warp % 7;
            float cg[2][4], cu[2][4];
#pragma unroll
            for (int n = 0; n < 2; n++) { cg[n][0] = cg[n][1] = cg[n][2] = cg[n][3] = 0.f; cu[n][0] = cu[n][1] = cu[n][2] = cu[n][3] = 0.f; }
#pragma unroll
            for (int i = 0; i < 2; i++) {
                const int ks = 2 * kk + i, kgl = box * 224 + ks * 16;
                uint32_t a0 = 0, a2 = 0;
                if (g < 4) { a0 = lds32(xn_u + (g * XN_PITCH + kgl + 2 * tq) * 2); a2 = lds32(xn_u + (g * XN_PITCH + kgl + 8 + 2 * tq) * 2); }
                const int r = ks * 16 + (lane & 7) + ((lane >> 3) & 1) * 8;
                const int ch = lane >> 4;
                const uint32_t off = box * 7168 + r * 32 + ((ch ^ ((r >> 2) & 1)) << 4);
                uint32_t b0, b1, b2, b3;
                ldsm_x4_t(ring + sg * STAGE + off, b0, b1, b2, b3);
                mma_bf16(cg[0], a0, a2, b0, b1);
                mma_bf16(cg[1], a0, a2, b2, b3);
                ldsm_x4_t(ring + su * STAGE + off, b0, b1, b2, b3);
                mma_bf16(cu[0], a0, a2, b0, b1);
                mma_bf16(cu[1], a0, a2, b2, b3);
            }
            if (lane < 16) {
#pragma unroll
                for (int n = 0; n < 2; n++) {
                    *reinterpret_cast<float2*>(red + (warp * 4 + g) * 32 + n * 8 + 2 * tq) = make_float2(cg[n][0], cg[n][1]);
                    *reinterpret_cast<float2*>(red + (warp * 4 + g) * 32 + 16 + n * 8 + 2 * tq) = make_float2(cu[n][0], cu[n][1]);
                }
            }
        }
        cons_bar();
        if (t < 64) {
            const int bb = t >> 4, f = t & 15;
            float sg_ = 0.f, su_ = 0.f;
#pragma unroll
            for (int w = 0; w < 14; w++) { sg_ += red[(w * 4 + bb) * 32 + f]; su_ += red[(w * 4 + bb) * 32 + 16 + f]; }
            const float gv = rbf(sg_), uv = rbf(su_);
            const float inner = 0.7978845608028654f * (gv + 0.044715f * gv * gv * gv);
            const float gl = rbf(0.5f * gv * (1.f + tanhf(inner)));
            h_bf[bb * H_PITCH + f] = __float2bfloat16_rn(gl * uv);
        }
        cons_bar();
        mbar_wait(smem_u32(&fullb[sd]), (20 / NSTAGE) & 1);
        if (warp < 14) {
            const int jb = warp >> 1, cb = (warp & 1) * 4;
            const uint32_t h_u = smem_u32(h_bf);
            uint32_t a0 = 0, a2 = 0;
            if (g < 4) { a0 = lds32(h_u + (g * H_PITCH + 2 * tq) * 2); a2 = lds32(h_u + (g * H_PITCH + 8 + 2 * tq) * 2); }
            const int r = (lane & 7) + ((lane >> 3) & 1) * 8;
            float cc[4][4];
#pragma unroll
            for (int cp = 0; cp < 2; cp++) {
                const int ch = cb + 2 * cp + (lane >> 4);
                uint32_t b0, b1, b2, b3;
                ldsm_x4_t(ring + sd * STAGE + jb * 2048 + r * 128 + ((ch ^ (r & 7)) << 4), b0, b1, b2, b3);
                cc[2 * cp][0] = cc[2 * cp][1] = cc[2 * cp][2] = cc[2 * cp][3] = 0.f;
                cc[2 * cp + 1][0] = cc[2 * cp + 1][1] = cc[2 * cp + 1][2] = cc[2 * cp + 1][3] = 0.f;
                mma_bf16(cc[2 * cp], a0, a2, b0, b1);
                mma_bf16(cc[2 * cp + 1], a0, a2, b2, b3);
            }
            if (lane < 16) {
#pragma unroll
                for (int i = 0; i < 4; i++) *reinterpret_cast<float2*>(red + g * DM + jb * 64 + (cb + i) * 8 + 2 * tq) = make_float2(cc[i][0], cc[i][1]);
            }
        }
        cons_bar();
#pragma unroll
        for (int r = 0; r < 4; r++) {
            const int ep = t + 512 * r, j = ep >> 4, w = ep & 15;
            const float v = (w < 14) ? red[14 * j + w] : 1.0f;
            st_pub(&g_fbox[j][cta][16 + w], __float_as_uint(v) ^ KEYF);
        }
    }
    PROF(7);

    if (t < 128) {
        const int bb = t >> 5, d = t & 31;
        uint32_t v[4];
#pragma unroll
        for (int cc = 0; cc < 4; cc++) v[cc] = ld_poll(&g_obox[cta][bb * 4 + cc][d]);
        int itc = 0;
        bool pend;
        do {
            pend = false;
#pragma unroll
            for (int cc = 0; cc < 4; cc++) if (v[cc] == 0u) { v[cc] = ld_poll(&g_obox[cta][bb * 4 + cc][d]); pend |= (v[cc] == 0u); }
        } while (pend && ++itc < SPIN_CAP);
        float s = 0.f;
#pragma unroll
        for (int cc = 0; cc < 4; cc++) { st_pub(&g_obox[cta][bb * 4 + cc][d], 0u); s += __uint_as_float(v[cc] ^ KEYF); }
        o_bf[bb * O_PITCH + d] = __float2bfloat16_rn(s);
    }
    cons_bar();
    PROF(8);

    if (warp < 14) {
        const int jb = warp >> 1, cb = (warp & 1) * 4;
        const int it = IT_WO + (jb >> 2), slot = it % NSTAGE;
        const uint32_t o_u = smem_u32(o_bf);
        uint32_t a0[2] = {0, 0}, a2[2] = {0, 0};
        if (g < 4) {
#pragma unroll
            for (int ks = 0; ks < 2; ks++) { a0[ks] = lds32(o_u + (g * O_PITCH + ks * 16 + 2 * tq) * 2); a2[ks] = lds32(o_u + (g * O_PITCH + ks * 16 + 8 + 2 * tq) * 2); }
        }
        mbar_wait(smem_u32(&fullb[slot]), (it / NSTAGE) & 1);
        const uint32_t bb = ring + slot * STAGE + (jb & 3) * 4096;
        float cc[4][4];
#pragma unroll
        for (int n = 0; n < 4; n++) { cc[n][0] = cc[n][1] = cc[n][2] = cc[n][3] = 0.f; }
#pragma unroll
        for (int ks = 0; ks < 2; ks++) {
            const int r = ks * 16 + (lane & 7) + ((lane >> 3) & 1) * 8;
#pragma unroll
            for (int cp = 0; cp < 2; cp++) {
                const int ch = cb + 2 * cp + (lane >> 4);
                uint32_t b0, b1, b2, b3;
                ldsm_x4_t(bb + r * 128 + ((ch ^ (r & 7)) << 4), b0, b1, b2, b3);
                mma_bf16(cc[2 * cp], a0[ks], a2[ks], b0, b1);
                mma_bf16(cc[2 * cp + 1], a0[ks], a2[ks], b2, b3);
            }
        }
        if (lane < 16) {
#pragma unroll
            for (int i = 0; i < 4; i++) *reinterpret_cast<float2*>(red + g * DM + jb * 64 + (cb + i) * 8 + 2 * tq) = make_float2(cc[i][0], cc[i][1]);
        }
    }
    cons_bar();
#pragma unroll
    for (int r = 0; r < 4; r++) {
        const int ep = t + 512 * r, j = ep >> 4, w = ep & 15;
        const float v = (w < 14) ? red[14 * j + w] : 1.0f;
        st_pub(&g_fbox[j][cta][w], __float_as_uint(v) ^ KEYF);
    }
    PROF(9);

    if (t < 448) {
        const int o = t >> 4, part = t & 15;
        const int w = (o < 14) ? o : o + 2;
        uint32_t* base = &g_fbox[cta][part][w];
        uint32_t v[8];
#pragma unroll
        for (int m = 0; m < 8; m++) {
            const bool need = (o < 14) || (((m * 16 + part) & 7) != 7);
            v[m] = need ? ld_poll(base + m * 16 * 32) : KEYF;
        }
        int itc = 0;
        bool pend;
        do {
            pend = false;
#pragma unroll
            for (int m = 0; m < 8; m++) if (v[m] == 0u) { v[m] = ld_poll(base + m * 16 * 32); pend |= (v[m] == 0u); }
        } while (pend && ++itc < SPIN_CAP);
        float s = 0.f;
#pragma unroll
        for (int m = 0; m < 8; m++) { if (v[m] != KEYF) st_pub(base + m * 16 * 32, 0u); s += __uint_as_float(v[m] ^ KEYF); }
        s += __shfl_xor_sync(0xffffffffu, s, 8);
        s += __shfl_xor_sync(0xffffffffu, s, 4);
        s += __shfl_xor_sync(0xffffffffu, s, 2);
        s += __shfl_xor_sync(0xffffffffu, s, 1);
        if (part == 0) fin_s[o] = s;
    }
    cons_bar();
    if (t < 14) {
        const float A = rbf(fin_s[t]), Bv = rbf(fin_s[14 + t]);
        out[cta * 14 + t] = __float2bfloat16_rn(rbf(x_res + A) + Bv);
    }
    PROF(10);
}

typedef CUresult (*EncodeTiledFn)(CUtensorMap*, CUtensorMapDataType, cuuint32_t, void*, const cuuint64_t*, const cuuint64_t*,
                                  const cuuint32_t*, const cuuint32_t*, CUtensorMapInterleave, CUtensorMapSwizzle,
                                  CUtensorMapL2promotion, CUtensorMapFloatOOBfill);

bool make_map(EncodeTiledFn enc, CUtensorMap* m, const void* ptr, uint64_t inner, uint64_t outer, uint64_t pitch_bytes,
              uint32_t box_inner, uint32_t box_outer, CUtensorMapSwizzle swz) {
    cuuint64_t dims[2] = {inner, outer};
    cuuint64_t strides[1] = {pitch_bytes};
    cuuint32_t box[2] = {box_inner, box_outer};
    cuuint32_t estr[2] = {1, 1};
    return enc(m, CU_TENSOR_MAP_DATA_TYPE_BFLOAT16, 2, const_cast<void*>(ptr), dims, strides, box, estr,
               CU_TENSOR_MAP_INTERLEAVE_NONE, swz, CU_TENSOR_MAP_L2_PROMOTION_NONE, CU_TENSOR_MAP_FLOAT_OOB_FILL_NONE) == CUDA_SUCCESS;
}

}

extern "C" void kernel_launch(void* const* d_in, const int* in_sizes, int n_in, void* d_out, int out_size) {
    (void)in_sizes; (void)n_in; (void)out_size;
    const bf16* x = (const bf16*)d_in[0];
    void* fn = nullptr;
    cudaDriverEntryPointQueryResult qr;
    if (cudaGetDriverEntryPoint("cuTensorMapEncodeTiled", &fn, cudaEnableDefault, &qr) != cudaSuccess || fn == nullptr) return;
    EncodeTiledFn enc = (EncodeTiledFn)fn;
    Maps tm;
    bool ok = true;
    ok &= make_map(enc, &tm.k, d_in[1], DH, (uint64_t)4 * HKV * SK, DH * 2, 64, 32, CU_TENSOR_MAP_SWIZZLE_128B);
    ok &= make_map(enc, &tm.v, d_in[2], DH, (uint64_t)4 * HKV * SK, DH * 2, 64, 32, CU_TENSOR_MAP_SWIZZLE_128B);
    ok &= make_map(enc, &tm.wq, d_in[3], 4096, DM, 4096 * 2, 32, 224, CU_TENSOR_MAP_SWIZZLE_64B);
    ok &= make_map(enc, &tm.wo, d_in[4], DM, 4096, DM * 2, 64, 32, CU_TENSOR_MAP_SWIZZLE_128B);
    ok &= make_map(enc, &tm.wg, d_in[6], FF, DM, FF * 2, 16, 224, CU_TENSOR_MAP_SWIZZLE_32B);
    ok &= make_map(enc, &tm.wu, d_in[7], FF, DM, FF * 2, 16, 224, CU_TENSOR_MAP_SWIZZLE_32B);
    ok &= make_map(enc, &tm.wd, d_in[8], DM, FF, DM * 2, 64, 16, CU_TENSOR_MAP_SWIZZLE_128B);
    if (!ok) return;
    cudaFuncSetAttribute(fused_decode_kernel, cudaFuncAttributeMaxDynamicSharedMemorySize, SM_TOTAL);
    fused_decode_kernel<<<NCTA, NTHREADS, SM_TOTAL>>>(tm, x, (bf16*)d_out);
}
```

```cpp
#include <cuda_runtime.h>
#include <cuda_bf16.h>
#include <cuda.h>
#include <stdint.h>

namespace {

typedef __nv_bfloat16 bf16;

constexpr int DM = 448, HKV = 8, SK = 4096, DH = 256, WIN = 1024, FF = 1792;
constexpr int NCTA = 128;
constexpr int NCW = 16;
constexpr int NCONS = NCW * 32;
constexpr int NTHREADS = NCONS + 32;
constexpr int STAGE = 16384;
constexpr int NSTAGE = 12;
#define INFLIGHT_ITEMS 3
constexpr int INFLIGHT = INFLIGHT_ITEMS;
#define PROD_DELAY 300
#define X_FIRST 0
constexpr uint32_t KEYF = 0xFFF0DEADu;
constexpr uint32_t KEYB = 0xFFADFFADu;
constexpr int SPIN_CAP = 1 << 21;

__device__ uint32_t g_qbox[NCTA][256];
__device__ uint32_t g_sbox[NCTA][4][2][8];
__device__ uint32_t g_obox[NCTA][16][32];
__device__ uint32_t g_fbox[NCTA][NCTA][32];

#define PROF(n) do { } while (0)

constexpr int XN_PITCH = 456, QP_PITCH = 264, H_PITCH = 24, O_PITCH = 40;
constexpr int SM_RING = 0;
constexpr int SM_BAR = NSTAGE * STAGE;
constexpr int SM_XN = SM_BAR + 256;
constexpr int SM_RED = SM_XN + 4 * XN_PITCH * 2;
constexpr int SM_RED2 = SM_RED + 8192;
constexpr int SM_Q = SM_RED2 + 8192;
constexpr int SM_P = SM_Q + 2 * QP_PITCH * 2;
constexpr int SM_SC = SM_P + 2 * QP_PITCH * 2;
constexpr int SM_H = SM_SC + 2048;
constexpr int SM_O = SM_H + 4 * H_PITCH * 2;
constexpr int SM_ST = SM_O + 4 * O_PITCH * 2;
constexpr int SM_FIN = SM_ST + 32;
constexpr int SM_TOTAL = SM_FIN + 128;
static_assert(SM_TOTAL <= 232448, "smem");

__device__ __forceinline__ float rbf(float x) { return __bfloat162float(__float2bfloat16_rn(x)); }
__device__ __forceinline__ uint32_t smem_u32(const void* p) { return (uint32_t)__cvta_generic_to_shared(p); }
__device__ __forceinline__ void mbar_init(uint32_t bar, uint32_t cnt) {
    asm volatile("mbarrier.init.shared::cta.b64 [%0], %1;" :: "r"(bar), "r"(cnt) : "memory");
}
__device__ __forceinline__ void mbar_expect_tx(uint32_t bar, uint32_t bytes) {
    asm volatile("mbarrier.arrive.expect_tx.shared::cta.b64 _, [%0], %1;" :: "r"(bar), "r"(bytes) : "memory");
}
__device__ __forceinline__ void mbar_arrive(uint32_t bar) {
    asm volatile("mbarrier.arrive.shared::cta.b64 _, [%0];" :: "r"(bar) : "memory");
}
__device__ __forceinline__ bool mbar_try_wait(uint32_t bar, uint32_t parity) {
    uint32_t ok;
    asm volatile("{\n.reg .pred p;\nmbarrier.try_wait.parity.shared::cta.b64 p, [%1], %2;\nselp.u32 %0, 1, 0, p;\n}"
                 : "=r"(ok) : "r"(bar), "r"(parity) : "memory");
    return ok;
}
__device__ __forceinline__ void mbar_wait(uint32_t bar, uint32_t parity) {
    int it = 0;
    while (!mbar_try_wait(bar, parity)) { if (++it > SPIN_CAP) break; }
}
__device__ __forceinline__ void tma2d(uint32_t dst, const CUtensorMap* tm, int c0, int c1, uint32_t bar) {
    asm volatile("cp.async.bulk.tensor.2d.shared::cluster.global.mbarrier::complete_tx::bytes [%0], [%1, {%2, %3}], [%4];"
                 :: "r"(dst), "l"(tm), "r"(c0), "r"(c1), "r"(bar) : "memory");
}
__device__ __forceinline__ uint32_t ld_poll(const uint32_t* p) {
    uint32_t v; asm volatile("ld.relaxed.gpu.global.u32 %0, [%1];" : "=r"(v) : "l"(p) : "memory"); return v;
}
__device__ __forceinline__ void st_pub(uint32_t* p, uint32_t v) {
    asm volatile("st.relaxed.gpu.global.u32 [%0], %1;" :: "l"(p), "r"(v) : "memory");
}
__device__ __forceinline__ void st_pub2(uint32_t* p, uint32_t v0, uint32_t v1) {
    asm volatile("st.relaxed.gpu.global.v2.u32 [%0], {%1, %2};" :: "l"(p), "r"(v0), "r"(v1) : "memory");
}
__device__ __forceinline__ uint4 ld_poll4(const uint32_t* p) {
    uint4 v; asm volatile("ld.relaxed.gpu.global.v4.u32 {%0,%1,%2,%3}, [%4];" : "=r"(v.x), "=r"(v.y), "=r"(v.z), "=r"(v.w) : "l"(p) : "memory"); return v;
}
__device__ __forceinline__ void st_pub4(uint32_t* p, uint32_t a, uint32_t b, uint32_t c, uint32_t d) {
    asm volatile("st.relaxed.gpu.global.v4.u32 [%0], {%1,%2,%3,%4};" :: "l"(p), "r"(a), "r"(b), "r"(c), "r"(d) : "memory");
}
__device__ __forceinline__ uint32_t poll_word(uint32_t* p) {
    uint32_t v = ld_poll(p);
    int it = 0;
    while (v == 0u) { if (++it > SPIN_CAP) break; v = ld_poll(p); }
    st_pub(p, 0u);
    return v;
}
__device__ __forceinline__ void cons_bar() { asm volatile("bar.sync 1, 512;" ::: "memory"); }
__device__ __forceinline__ float warp_sum(float v) {
#pragma unroll
    for (int o = 16; o > 0; o >>= 1) v += __shfl_xor_sync(0xffffffffu, v, o);
    return v;
}
__device__ __forceinline__ float warp_max(float v) {
#pragma unroll
    for (int o = 16; o > 0; o >>= 1) v = fmaxf(v, __shfl_xor_sync(0xffffffffu, v, o));
    return v;
}
__device__ __forceinline__ uint32_t lds32(uint32_t addr) {
    uint32_t v; asm volatile("ld.shared.b32 %0, [%1];" : "=r"(v) : "r"(addr)); return v;
}
__device__ __forceinline__ void ldsm_x4(uint32_t addr, uint32_t& r0, uint32_t& r1, uint32_t& r2, uint32_t& r3) {
    asm volatile("ldmatrix.sync.aligned.m8n8.x4.shared.b16 {%0,%1,%2,%3}, [%4];"
                 : "=r"(r0), "=r"(r1), "=r"(r2), "=r"(r3) : "r"(addr) : "memory");
}
__device__ __forceinline__ void ldsm_x4_t(uint32_t addr, uint32_t& r0, uint32_t& r1, uint32_t& r2, uint32_t& r3) {
    asm volatile("ldmatrix.sync.aligned.m8n8.x4.trans.shared.b16 {%0,%1,%2,%3}, [%4];"
                 : "=r"(r0), "=r"(r1), "=r"(r2), "=r"(r3) : "r"(addr) : "memory");
}
__device__ __forceinline__ void mma_bf16(float (&c)[4], uint32_t a0, uint32_t a2, uint32_t b0, uint32_t b1) {
    asm volatile("mma.sync.aligned.m16n8k16.row.col.f32.bf16.bf16.f32 {%0,%1,%2,%3}, {%4,%5,%6,%7}, {%8,%9}, {%0,%1,%2,%3};"
                 : "+f"(c[0]), "+f"(c[1]), "+f"(c[2]), "+f"(c[3])
                 : "r"(a0), "r"(0u), "r"(a2), "r"(0u), "r"(b0), "r"(b1));
}

struct Maps { CUtensorMap k, v, wq, wg, wu, wd, wo; };

__global__ void __launch_bounds__(NTHREADS, 1)
fused_decode_kernel(const __grid_constant__ Maps tm, const bf16* __restrict__ x, bf16* __restrict__ out) {
    extern __shared__ __align__(1024) unsigned char smem[];
    const uint32_t ring = smem_u32(smem + SM_RING);
    uint64_t* fullb = reinterpret_cast<uint64_t*>(smem + SM_BAR);
    uint64_t* emptyb = fullb + NSTAGE;
    uint64_t* xbar = emptyb + NSTAGE;
    bf16* xn_bf = reinterpret_cast<bf16*>(smem + SM_XN);
    float* red = reinterpret_cast<float*>(smem + SM_RED);
    float* red2 = reinterpret_cast<float*>(smem + SM_RED2);
    bf16* q_bf = reinterpret_cast<bf16*>(smem + SM_Q);
    bf16* p_bf = reinterpret_cast<bf16*>(smem + SM_P);
    float* sc_s = reinterpret_cast<float*>(smem + SM_SC);
    bf16* h_bf = reinterpret_cast<bf16*>(smem + SM_H);
    bf16* o_bf = reinterpret_cast<bf16*>(smem + SM_O);
    float* st_s = reinterpret_cast<float*>(smem + SM_ST);
    float* fin_s = reinterpret_cast<float*>(smem + SM_FIN);

    const int cta = blockIdx.x;
    const int kvh = cta >> 4, b = (cta >> 2) & 3, c = cta & 3;
    const bool ffn = (cta & 7) != 7;
    const int fi = (cta >> 3) * 7 + (cta & 7);
    const int t = threadIdx.x, warp = t >> 5, lane = t & 31;
    const int g = lane >> 2, tq = lane & 3;
    const int IT_K = 2 + (ffn ? 3 : 0);
    const int IT_V = IT_K + 8;
    const int IT_WO = IT_V + 8;
    const int NITEMS = IT_WO + 2;

    if (t == 0) {
        for (int s = 0; s < NSTAGE; s++) {
            mbar_init(smem_u32(&fullb[s]), 1);
            mbar_init(smem_u32(&emptyb[s]), NCW);
        }
        mbar_init(smem_u32(xbar), 4);
        asm volatile("fence.mbarrier_init.release.cluster;" ::: "memory");
    }
    __syncthreads();

    if (warp == NCW) {
        if (lane == 0) {
            const int kvrow = (b * HKV + kvh) * SK + (SK - WIN) + c * 256;
            __nanosleep(PROD_DELAY);
            for (int it = 0; it < NITEMS; it++) {
                const int slot = it % NSTAGE;
                const uint32_t dst = ring + slot * STAGE, fb = smem_u32(&fullb[slot]);
                if (it >= NSTAGE) mbar_wait(smem_u32(&emptyb[slot]), ((it / NSTAGE) - 1) & 1);
                if (it >= INFLIGHT) { const int j = it - INFLIGHT; mbar_wait(smem_u32(&fullb[j % NSTAGE]), (j / NSTAGE) & 1); }
                if (it < 2) {
                    mbar_expect_tx(fb, 224 * 64);
                    tma2d(dst, &tm.wq, 32 * cta, 224 * it, fb);
                } else if (it >= IT_K && it < IT_WO) {
                    const CUtensorMap* m = it < IT_V ? &tm.k : &tm.v;
                    const int row = kvrow + (it < IT_V ? it - IT_K : it - IT_V) * 32;
                    mbar_expect_tx(fb, STAGE);
#pragma unroll
                    for (int j = 0; j < 4; j++) tma2d(dst + j * 4096, m, 64 * j, row, fb);
                } else if (it < IT_K) {
                    if (it < 4) {
                        const CUtensorMap* m = it == 2 ? &tm.wg : &tm.wu;
                        mbar_expect_tx(fb, 2 * 224 * 32);
                        tma2d(dst, m, 16 * fi, 0, fb);
                        tma2d(dst + 7168, m, 16 * fi, 224, fb);
                    } else {
                        mbar_expect_tx(fb, 7 * 2048);
#pragma unroll
                        for (int j = 0; j < 7; j++) tma2d(dst + j * 2048, &tm.wd, 64 * j, 16 * fi, fb);
                    }
                } else {
                    const int j0 = (it - IT_WO) * 4, nj = (it == IT_WO) ? 4 : 3;
                    mbar_expect_tx(fb, nj * 4096);
                    for (int j = 0; j < nj; j++) tma2d(dst + j * 4096, &tm.wo, 64 * (j0 + j), 32 * cta, fb);
                }
            }
        }
        return;
    }

    PROF(0);
    float x_res = 0.f;
    if (t < 14) x_res = __bfloat162float(x[cta * 14 + t]);

    if (warp < 4) {
        float xv[14], sum = 0.f;
#pragma unroll
        for (int j = 0; j < 14; j++) { xv[j] = __bfloat162float(x[warp * DM + lane + 32 * j]); sum += xv[j]; }
        sum = warp_sum(sum);
        if (lane == 0) mbar_arrive(smem_u32(xbar));
        const float mean = sum / 448.f;
        const float m_bf = rbf(mean);
        float ss = 0.f;
#pragma unroll
        for (int j = 0; j < 14; j++) { const float d = xv[j] - mean; ss = fmaf(d, d, ss); }
        ss = warp_sum(ss);
        const float v_bf = rbf(ss / 448.f);
        const float den = rbf(__fsqrt_rn(rbf(v_bf + 1e-5f)));
#pragma unroll
        for (int j = 0; j < 14; j++) xn_bf[warp * XN_PITCH + lane + 32 * j] = __float2bfloat16_rn(__fdiv_rn(rbf(xv[j] - m_bf), den));
    }
    cons_bar();
    PROF(1);
    const uint32_t xn_u = smem_u32(xn_bf);

    mbar_wait(smem_u32(&fullb[0]), 0);
    mbar_wait(smem_u32(&fullb[1]), 0);
    if (warp < 14) {
        const int box = warp / 7, kk = warp % 7;
        const uint32_t base = ring + box * STAGE;
        float cc[4][4];
#pragma unroll
        for (int n = 0; n < 4; n++) { cc[n][0] = cc[n][1] = cc[n][2] = cc[n][3] = 0.f; }
#pragma unroll
        for (int i = 0; i < 2; i++) {
            const int ks = 2 * kk + i, kgl = box * 224 + ks * 16;
            uint32_t a0 = 0, a2 = 0;
            if (g < 4) { a0 = lds32(xn_u + (g * XN_PITCH + kgl + 2 * tq) * 2); a2 = lds32(xn_u + (g * XN_PITCH + kgl + 8 + 2 * tq) * 2); }
            const int r = ks * 16 + (lane & 7) + ((lane >> 3) & 1) * 8;
#pragma unroll
            for (int cp = 0; cp < 2; cp++) {
                const int ch = 2 * cp + (lane >> 4);
                uint32_t b0, b1, b2, b3;
                ldsm_x4_t(base + r * 64 + ((ch ^ ((r >> 1) & 3)) << 4), b0, b1, b2, b3);
                mma_bf16(cc[2 * cp], a0, a2, b0, b1);
                mma_bf16(cc[2 * cp + 1], a0, a2, b2, b3);
            }
        }
        if (lane < 16) {
#pragma unroll
            for (int n = 0; n < 4; n++) *reinterpret_cast<float2*>(red + (warp * 4 + g) * 32 + n * 8 + 2 * tq) = make_float2(cc[n][0], cc[n][1]);
        }
    }
    __syncwarp();
    if (lane == 0) { mbar_arrive(smem_u32(&emptyb[0])); mbar_arrive(smem_u32(&emptyb[1])); }
    cons_bar();
    if (t < 128) {
        const int bb = t >> 5, col = t & 31;
        float s = 0.f;
#pragma unroll
        for (int w = 0; w < 14; w++) s += red[(w * 4 + bb) * 32 + col];
        const float s2 = __shfl_down_sync(0xffffffffu, s, 1);
        if ((col & 1) == 0) {
            __nv_bfloat162 pk = __floats2bfloat162_rn(s, s2);
            const uint32_t wv = (*reinterpret_cast<uint32_t*>(&pk)) ^ KEYB;
#pragma unroll
            for (int cc2 = 0; cc2 < 4; cc2++) st_pub(&g_qbox[kvh * 16 + bb * 4 + cc2][(cta & 15) * 16 + (col >> 1)], wv);
        }
    }
    PROF(2);

    if (ffn) {
        const int sg = 2, su = 3, sd = 4;
        mbar_wait(smem_u32(&fullb[sg]), 0);
        mbar_wait(smem_u32(&fullb[su]), 0);
        if (warp < 14) {
            const int box = warp / 7, kk = warp % 7;
            float cg[2][4], cu[2][4];
#pragma unroll
            for (int n = 0; n < 2; n++) { cg[n][0] = cg[n][1] = cg[n][2] = cg[n][3] = 0.f; cu[n][0] = cu[n][1] = cu[n][2] = cu[n][3] = 0.f; }
#pragma unroll
            for (int i = 0; i < 2; i++) {
                const int ks = 2 * kk + i, kgl = box * 224 + ks * 16;
                uint32_t a0 = 0, a2 = 0;
                if (g < 4) { a0 = lds32(xn_u + (g * XN_PITCH + kgl + 2 * tq) * 2); a2 = lds32(xn_u + (g * XN_PITCH + kgl + 8 + 2 * tq) * 2); }
                const int r = ks * 16 + (lane & 7) + ((lane >> 3) & 1) * 8;
                const int ch = lane >> 4;
                const uint32_t off = box * 7168 + r * 32 + ((ch ^ ((r >> 2) & 1)) << 4);
                uint32_t b0, b1, b2, b3;
                ldsm_x4_t(ring + sg * STAGE + off, b0, b1, b2, b3);
                mma_bf16(cg[0], a0, a2, b0, b1);
                mma_bf16(cg[1], a0, a2, b2, b3);
                ldsm_x4_t(ring + su * STAGE + off, b0, b1, b2, b3);
                mma_bf16(cu[0], a0, a2, b0, b1);
                mma_bf16(cu[1], a0, a2, b2, b3);
            }
            if (lane < 16) {
#pragma unroll
                for (int n = 0; n < 2; n++) {
                    *reinterpret_cast<float2*>(red2 + (warp * 4 + g) * 32 + n * 8 + 2 * tq) = make_float2(cg[n][0], cg[n][1]);
                    *reinterpret_cast<float2*>(red2 + (warp * 4 + g) * 32 + 16 + n * 8 + 2 * tq) = make_float2(cu[n][0], cu[n][1]);
                }
            }
        }
        __syncwarp();
        if (lane == 0) { mbar_arrive(smem_u32(&emptyb[sg])); mbar_arrive(smem_u32(&emptyb[su])); }
        cons_bar();
        if (t < 64) {
            const int bb = t >> 4, f = t & 15;
            float sg_ = 0.f, su_ = 0.f;
#pragma unroll
            for (int w = 0; w < 14; w++) { sg_ += red2[(w * 4 + bb) * 32 + f]; su_ += red2[(w * 4 + bb) * 32 + 16 + f]; }
            const float gv = rbf(sg_), uv = rbf(su_);
            const float inner = 0.7978845608028654f * (gv + 0.044715f * gv * gv * gv);
            const float gl = rbf(0.5f * gv * (1.f + tanhf(inner)));
            h_bf[bb * H_PITCH + f] = __float2bfloat16_rn(gl * uv);
        }
        cons_bar();
        mbar_wait(smem_u32(&fullb[sd]), 0);
        if (warp < 14) {
            const int jb = warp >> 1, cb = (warp & 1) * 4;
            const uint32_t h_u = smem_u32(h_bf);
            uint32_t a0 = 0, a2 = 0;
            if (g < 4) { a0 = lds32(h_u + (g * H_PITCH + 2 * tq) * 2); a2 = lds32(h_u + (g * H_PITCH + 8 + 2 * tq) * 2); }
            const int r = (lane & 7) + ((lane >> 3) & 1) * 8;
            float cc[4][4];
#pragma unroll
            for (int cp = 0; cp < 2; cp++) {
                const int ch = cb + 2 * cp + (lane >> 4);
                uint32_t b0, b1, b2, b3;
                ldsm_x4_t(ring + sd * STAGE + jb * 2048 + r * 128 + ((ch ^ (r & 7)) << 4), b0, b1, b2, b3);
                cc[2 * cp][0] = cc[2 * cp][1] = cc[2 * cp][2] = cc[2 * cp][3] = 0.f;
                cc[2 * cp + 1][0] = cc[2 * cp + 1][1] = cc[2 * cp + 1][2] = cc[2 * cp + 1][3] = 0.f;
                mma_bf16(cc[2 * cp], a0, a2, b0, b1);
                mma_bf16(cc[2 * cp + 1], a0, a2, b2, b3);
            }
            if (lane < 16) {
#pragma unroll
                for (int i = 0; i < 4; i++) *reinterpret_cast<float2*>(red2 + g * DM + jb * 64 + (cb + i) * 8 + 2 * tq) = make_float2(cc[i][0], cc[i][1]);
            }
        }
        __syncwarp();
        if (lane == 0) mbar_arrive(smem_u32(&emptyb[sd]));
        cons_bar();
#pragma unroll
        for (int r = 0; r < 4; r++) {
            const int ep = t + 512 * r, j = ep >> 4, w = ep & 15;
            const float v = (w < 14) ? red2[14 * j + w] : 1.0f;
            st_pub(&g_fbox[j][cta][16 + w], __float_as_uint(v) ^ KEYF);
        }
    }

    if (t < 256) {
        const uint32_t v = poll_word(&g_qbox[cta][t]) ^ KEYB;
        *reinterpret_cast<uint32_t*>(q_bf + (t >> 7) * QP_PITCH + 2 * (t & 127)) = v;
    }
    cons_bar();
    PROF(3);

    {
        const uint32_t q_u = smem_u32(q_bf);
        const int nt = warp & 3, kq = warp >> 2;
        uint32_t qa[4][2];
#pragma unroll
        for (int ks = 0; ks < 4; ks++) {
            qa[ks][0] = 0; qa[ks][1] = 0;
            if (g < 2) { qa[ks][0] = lds32(q_u + (g * QP_PITCH + kq * 64 + ks * 16 + 2 * tq) * 2); qa[ks][1] = lds32(q_u + (g * QP_PITCH + kq * 64 + ks * 16 + 8 + 2 * tq) * 2); }
        }
        const int row = nt * 8 + (lane & 7);
#pragma unroll 1
        for (int s = 0; s < 8; s++) {
            const int it = IT_K + s, slot = it % NSTAGE;
            mbar_wait(smem_u32(&fullb[slot]), (it / NSTAGE) & 1);
            const uint32_t bb = ring + slot * STAGE + kq * 4096 + row * 128;
            float cc[4] = {0.f, 0.f, 0.f, 0.f};
#pragma unroll
            for (int i = 0; i < 2; i++) {
                const int ch = 4 * i + (lane >> 3);
                uint32_t r0, r1, r2, r3;
                ldsm_x4(bb + ((ch ^ (lane & 7)) << 4), r0, r1, r2, r3);
                mma_bf16(cc, qa[2 * i][0], qa[2 * i][1], r0, r1);
                mma_bf16(cc, qa[2 * i + 1][0], qa[2 * i + 1][1], r2, r3);
            }
            if (lane < 8) *reinterpret_cast<float2*>(red + (kq * 2 + g) * 256 + s * 32 + nt * 8 + 2 * tq) = make_float2(cc[0], cc[1]);
            __syncwarp();
            if (lane == 0) mbar_arrive(smem_u32(&emptyb[slot]));
        }
    }
    cons_bar();
    PROF(4);

    if (warp < 2) {
        const int h = warp;
        float sv[8];
#pragma unroll
        for (int half = 0; half < 2; half++) {
            float4 a = *reinterpret_cast<const float4*>(red + (0 * 2 + h) * 256 + lane * 8 + half * 4);
#pragma unroll
            for (int kq = 1; kq < 4; kq++) {
                const float4 v = *reinterpret_cast<const float4*>(red + (kq * 2 + h) * 256 + lane * 8 + half * 4);
                a.x += v.x; a.y += v.y; a.z += v.z; a.w += v.w;
            }
            sv[half * 4 + 0] = rbf(a.x) * 0.0625f; sv[half * 4 + 1] = rbf(a.y) * 0.0625f;
            sv[half * 4 + 2] = rbf(a.z) * 0.0625f; sv[half * 4 + 3] = rbf(a.w) * 0.0625f;
            *reinterpret_cast<float4*>(sc_s + h * 256 + lane * 8 + half * 4) = make_float4(sv[half * 4], sv[half * 4 + 1], sv[half * 4 + 2], sv[half * 4 + 3]);
        }
        float m = sv[0];
#pragma unroll
        for (int j = 1; j < 8; j++) m = fmaxf(m, sv[j]);
        m = warp_max(m);
        float l = 0.f;
#pragma unroll
        for (int j = 0; j < 8; j++) l += expf(sv[j] - m);
        l = warp_sum(l);
        {
            const int w = lane & 7;
            const float v = (w == 0) ? m : (w == 1) ? l : 1.0f;
            st_pub(&g_sbox[(cta & ~3) + (lane >> 3)][c][h][w], __float_as_uint(v) ^ KEYF);
        }
    }

    {
        const int pi = t >> 2, qd = t & 3;
        uint32_t* pb = &g_fbox[cta][pi][16 + 4 * qd];
        uint4 vb = make_uint4(KEYF, KEYF, KEYF, KEYF);
        if ((pi & 7) != 7) {
            vb = ld_poll4(pb);
            int itc = 0;
            while ((vb.x == 0u || vb.y == 0u || vb.z == 0u || vb.w == 0u) && ++itc < SPIN_CAP) vb = ld_poll4(pb);
            st_pub4(pb, 0u, 0u, 0u, 0u);
        }
        *reinterpret_cast<float4*>(red2 + pi * 16 + 4 * qd) =
            make_float4(__uint_as_float(vb.x ^ KEYF), __uint_as_float(vb.y ^ KEYF), __uint_as_float(vb.z ^ KEYF), __uint_as_float(vb.w ^ KEYF));
        cons_bar();
        if (t < 224) {
            const int o = t >> 4, part = t & 15;
            float sacc = 0.f;
#pragma unroll
            for (int m = 0; m < 8; m++) sacc += red2[(m * 16 + part) * 16 + o];
            sacc += __shfl_xor_sync(0xffffffffu, sacc, 8);
            sacc += __shfl_xor_sync(0xffffffffu, sacc, 4);
            sacc += __shfl_xor_sync(0xffffffffu, sacc, 2);
            sacc += __shfl_xor_sync(0xffffffffu, sacc, 1);
            if (part == 0) fin_s[14 + o] = sacc;
        }
    }

    if (warp < 2) {
        const int h = warp;
        float mine = 0.f;
        if (lane < 8) mine = __uint_as_float(poll_word(&g_sbox[cta][lane >> 1][h][lane & 1]) ^ KEYF);
        __syncwarp();
        float M = -INFINITY;
#pragma unroll
        for (int cc = 0; cc < 4; cc++) M = fmaxf(M, __shfl_sync(0xffffffffu, mine, cc * 2));
        float L = 0.f;
#pragma unroll
        for (int cc = 0; cc < 4; cc++) L += __shfl_sync(0xffffffffu, mine, cc * 2 + 1) * expf(__shfl_sync(0xffffffffu, mine, cc * 2) - M);
        if (lane == 0) { st_s[2 * h] = M; st_s[2 * h + 1] = L; }
    }
    cons_bar();
    {
        const int h = t >> 8, key = t & 255;
        p_bf[h * QP_PITCH + key] = __float2bfloat16_rn(__fdiv_rn(expf(sc_s[h * 256 + key] - st_s[2 * h]), st_s[2 * h + 1]));
    }
    cons_bar();
    PROF(5);

    {
        const uint32_t p_u = smem_u32(p_bf);
        const int jb = warp >> 2, cb = (warp & 3) * 2;
        float acc[2][4];
#pragma unroll
        for (int n = 0; n < 2; n++) { acc[n][0] = acc[n][1] = acc[n][2] = acc[n][3] = 0.f; }
        const int rl = (lane & 7) + ((lane >> 3) & 1) * 8, ch = cb + (lane >> 4);
#pragma unroll 1
        for (int s = 0; s < 8; s++) {
            const int it = IT_V + s, slot = it % NSTAGE;
            mbar_wait(smem_u32(&fullb[slot]), (it / NSTAGE) & 1);
            const uint32_t bb = ring + slot * STAGE + jb * 4096;
#pragma unroll
            for (int ks = 0; ks < 2; ks++) {
                uint32_t a0 = 0, a2 = 0;
                if (g < 2) { const int k0 = s * 32 + ks * 16; a0 = lds32(p_u + (g * QP_PITCH + k0 + 2 * tq) * 2); a2 = lds32(p_u + (g * QP_PITCH + k0 + 8 + 2 * tq) * 2); }
                const int r = ks * 16 + rl;
                uint32_t r0, r1, r2, r3;
                ldsm_x4_t(bb + r * 128 + ((ch ^ (r & 7)) << 4), r0, r1, r2, r3);
                mma_bf16(acc[0], a0, a2, r0, r1);
                mma_bf16(acc[1], a0, a2, r2, r3);
            }
            __syncwarp();
            if (lane == 0) mbar_arrive(smem_u32(&emptyb[slot]));
        }
        if (lane < 8) {
            uint32_t* dst = &g_obox[kvh * 16 + g * 8 + (warp >> 1)][b * 4 + c][(warp & 1) * 16 + 2 * tq];
            st_pub2(dst, __float_as_uint(acc[0][0]) ^ KEYF, __float_as_uint(acc[0][1]) ^ KEYF);
            st_pub2(dst + 8, __float_as_uint(acc[1][0]) ^ KEYF, __float_as_uint(acc[1][1]) ^ KEYF);
        }
    }
    PROF(6);

    PROF(7);

    if (t < 128) {
        const int bb = t >> 5, d = t & 31;
        uint32_t v[4];
#pragma unroll
        for (int cc = 0; cc < 4; cc++) v[cc] = ld_poll(&g_obox[cta][bb * 4 + cc][d]);
        int itc = 0;
        bool pend;
        do {
            pend = false;
#pragma unroll
            for (int cc = 0; cc < 4; cc++) if (v[cc] == 0u) { v[cc] = ld_poll(&g_obox[cta][bb * 4 + cc][d]); pend |= (v[cc] == 0u); }
        } while (pend && ++itc < SPIN_CAP);
        float s = 0.f;
#pragma unroll
        for (int cc = 0; cc < 4; cc++) { st_pub(&g_obox[cta][bb * 4 + cc][d], 0u); s += __uint_as_float(v[cc] ^ KEYF); }
        o_bf[bb * O_PITCH + d] = __float2bfloat16_rn(s);
    }
    cons_bar();
    PROF(8);

    if (warp < 14) {
        const int jb = warp >> 1, cb = (warp & 1) * 4;
        const int it = IT_WO + (jb >> 2), slot = it % NSTAGE;
        const uint32_t o_u = smem_u32(o_bf);
        uint32_t a0[2] = {0, 0}, a2[2] = {0, 0};
        if (g < 4) {
#pragma unroll
            for (int ks = 0; ks < 2; ks++) { a0[ks] = lds32(o_u + (g * O_PITCH + ks * 16 + 2 * tq) * 2); a2[ks] = lds32(o_u + (g * O_PITCH + ks * 16 + 8 + 2 * tq) * 2); }
        }
        mbar_wait(smem_u32(&fullb[slot]), (it / NSTAGE) & 1);
        const uint32_t bb = ring + slot * STAGE + (jb & 3) * 4096;
        float cc[4][4];
#pragma unroll
        for (int n = 0; n < 4; n++) { cc[n][0] = cc[n][1] = cc[n][2] = cc[n][3] = 0.f; }
#pragma unroll
        for (int ks = 0; ks < 2; ks++) {
            const int r = ks * 16 + (lane & 7) + ((lane >> 3) & 1) * 8;
#pragma unroll
            for (int cp = 0; cp < 2; cp++) {
                const int ch = cb + 2 * cp + (lane >> 4);
                uint32_t b0, b1, b2, b3;
                ldsm_x4_t(bb + r * 128 + ((ch ^ (r & 7)) << 4), b0, b1, b2, b3);
                mma_bf16(cc[2 * cp], a0[ks], a2[ks], b0, b1);
                mma_bf16(cc[2 * cp + 1], a0[ks], a2[ks], b2, b3);
            }
        }
        if (lane < 16) {
#pragma unroll
            for (int i = 0; i < 4; i++) *reinterpret_cast<float2*>(red + g * DM + jb * 64 + (cb + i) * 8 + 2 * tq) = make_float2(cc[i][0], cc[i][1]);
        }
    }
    cons_bar();
#pragma unroll
    for (int r = 0; r < 4; r++) {
        const int ep = t + 512 * r, j = ep >> 4, w = ep & 15;
        const float v = (w < 14) ? red[14 * j + w] : 1.0f;
        st_pub(&g_fbox[j][cta][w], __float_as_uint(v) ^ KEYF);
    }
    PROF(9);

    {
        float* fbuf = reinterpret_cast<float*>(smem + SM_RING);
        const int pi = t >> 2, qd = t & 3;
        uint32_t* pa = &g_fbox[cta][pi][4 * qd];
        uint4 va = ld_poll4(pa);
        int itc = 0;
        while ((va.x == 0u || va.y == 0u || va.z == 0u || va.w == 0u) && ++itc < SPIN_CAP) va = ld_poll4(pa);
        st_pub4(pa, 0u, 0u, 0u, 0u);
        *reinterpret_cast<float4*>(fbuf + pi * 20 + 4 * qd) =
            make_float4(__uint_as_float(va.x ^ KEYF), __uint_as_float(va.y ^ KEYF), __uint_as_float(va.z ^ KEYF), __uint_as_float(va.w ^ KEYF));
        cons_bar();
        if (t < 224) {
            const int o = t >> 4, part = t & 15;
            float sacc = 0.f;
#pragma unroll
            for (int m = 0; m < 8; m++) sacc += fbuf[(m * 16 + part) * 20 + o];
            sacc += __shfl_xor_sync(0xffffffffu, sacc, 8);
            sacc += __shfl_xor_sync(0xffffffffu, sacc, 4);
            sacc += __shfl_xor_sync(0xffffffffu, sacc, 2);
            sacc += __shfl_xor_sync(0xffffffffu, sacc, 1);
            if (part == 0) fin_s[o] = sacc;
        }
    }
    cons_bar();
    if (t < 14) {
        const float A = rbf(fin_s[t]), Bv = rbf(fin_s[14 + t]);
        out[cta * 14 + t] = __float2bfloat16_rn(rbf(x_res + A) + Bv);
    }
    PROF(10);
}

typedef CUresult (*EncodeTiledFn)(CUtensorMap*, CUtensorMapDataType, cuuint32_t, void*, const cuuint64_t*, const cuuint64_t*,
                                  const cuuint32_t*, const cuuint32_t*, CUtensorMapInterleave, CUtensorMapSwizzle,
                                  CUtensorMapL2promotion, CUtensorMapFloatOOBfill);

bool make_map(EncodeTiledFn enc, CUtensorMap* m, const void* ptr, uint64_t inner, uint64_t outer, uint64_t pitch_bytes,
              uint32_t box_inner, uint32_t box_outer, CUtensorMapSwizzle swz) {
    cuuint64_t dims[2] = {inner, outer};
    cuuint64_t strides[1] = {pitch_bytes};
    cuuint32_t box[2] = {box_inner, box_outer};
    cuuint32_t estr[2] = {1, 1};
    return enc(m, CU_TENSOR_MAP_DATA_TYPE_BFLOAT16, 2, const_cast<void*>(ptr), dims, strides, box, estr,
               CU_TENSOR_MAP_INTERLEAVE_NONE, swz, CU_TENSOR_MAP_L2_PROMOTION_NONE, CU_TENSOR_MAP_FLOAT_OOB_FILL_NONE) == CUDA_SUCCESS;
}

}

extern "C" void kernel_launch(void* const* d_in, const int* in_sizes, int n_in, void* d_out, int out_size) {
    (void)in_sizes; (void)n_in; (void)out_size;
    const bf16* x = (const bf16*)d_in[0];
    void* fn = nullptr;
    cudaDriverEntryPointQueryResult qr;
    if (cudaGetDriverEntryPoint("cuTensorMapEncodeTiled", &fn, cudaEnableDefault, &qr) != cudaSuccess || fn == nullptr) return;
    EncodeTiledFn enc = (EncodeTiledFn)fn;
    Maps tm;
    bool ok = true;
    ok &= make_map(enc, &tm.k, d_in[1], DH, (uint64_t)4 * HKV * SK, DH * 2, 64, 32, CU_TENSOR_MAP_SWIZZLE_128B);
    ok &= make_map(enc, &tm.v, d_in[2], DH, (uint64_t)4 * HKV * SK, DH * 2, 64, 32, CU_TENSOR_MAP_SWIZZLE_128B);
    ok &= make_map(enc, &tm.wq, d_in[3], 4096, DM, 4096 * 2, 32, 224, CU_TENSOR_MAP_SWIZZLE_64B);
    ok &= make_map(enc, &tm.wo, d_in[4], DM, 4096, DM * 2, 64, 32, CU_TENSOR_MAP_SWIZZLE_128B);
    ok &= make_map(enc, &tm.wg, d_in[6], FF, DM, FF * 2, 16, 224, CU_TENSOR_MAP_SWIZZLE_32B);
    ok &= make_map(enc, &tm.wu, d_in[7], FF, DM, FF * 2, 16, 224, CU_TENSOR_MAP_SWIZZLE_32B);
    ok &= make_map(enc, &tm.wd, d_in[8], DM, FF, DM * 2, 64, 16, CU_TENSOR_MAP_SWIZZLE_128B);
    if (!ok) return;
    cudaFuncSetAttribute(fused_decode_kernel, cudaFuncAttributeMaxDynamicSharedMemorySize, SM_TOTAL);
    fused_decode_kernel<<<NCTA, NTHREADS, SM_TOTAL>>>(tm, x, (bf16*)d_out);
}
```
